```python
import torch

def _softmax(x, axis=-1):
    return torch.softmax(x, dim=axis)
def _gelu(x):
    return torch.nn.functional.gelu(x, approximate="tanh")
def _silu(x):
    return torch.nn.functional.silu(x)
def _sigmoid(x):
    return torch.sigmoid(x)
def _layernorm(x, axis=-1, eps=1e-5):
    m = x.mean(dim=axis, keepdim=True)
    v = x.var(dim=axis, keepdim=True, unbiased=False)
    return (x - m) / torch.sqrt(v + eps)
def _scatter_add(tgt, idx, src, axis=0):
    return tgt.clone().index_add_(axis, idx, src)
def _segment_sum(src, seg, n):
    out = torch.zeros((n,) + src.shape[1:], dtype=src.dtype)
    return out.index_add_(0, seg, src)
def _pad(x, pw):
    flat = tuple(v for pair in reversed(pw) for v in pair)
    return torch.nn.functional.pad(x, flat)

kernel_name = 'concat_heads__gqa_block_cached__gqa_block_cached__decode'

def setup_inputs():

    _w = (lambda a: (lambda t: t.to(torch.bfloat16) if t.is_floating_point() else t)(torch.as_tensor(a)))
    def _A_setup():
        B, Sq, D = 1, 1, 576
        Hq, Hkv, Sk, Dh = 32, 16, 8192, 128
        assert Hq % Hkv == 0, (Hq, Hkv)
        return {
            "x": _w((lambda *s: torch.randn(*s, dtype=torch.bfloat16) * 0.8)(B, Sq, D)),
            "k_cache": _w((lambda *s: torch.randn(*s, dtype=torch.bfloat16) * 0.8)(B, Hkv, Sk, Dh)),
            "v_cache": _w((lambda *s: torch.randn(*s, dtype=torch.bfloat16) * 0.05)(B, Hkv, Sk, Dh)),
            "wq": _w((lambda *s: torch.randn(*s, dtype=torch.bfloat16) * 0.8)(D, Hq * Dh) * (D ** -0.5)),
            "wo": _w((lambda *s: torch.randn(*s, dtype=torch.bfloat16) * 0.05)(Hq * Dh, D) * ((Hq * Dh) ** -0.5)),
        }
    _A_in = _A_setup()

    def _B_setup():
        B, Sq, D = 1, 1, 576
        Hq, Hkv, Sk, Dh = 32, 16, 8192, 128
        assert Hq % Hkv == 0, (Hq, Hkv)
        return {
            "x": _w((lambda *s: torch.randn(*s, dtype=torch.bfloat16) * 0.8)(B, Sq, D)),
            "k_cache": _w((lambda *s: torch.randn(*s, dtype=torch.bfloat16) * 0.8)(B, Hkv, Sk, Dh)),
            "v_cache": _w((lambda *s: torch.randn(*s, dtype=torch.bfloat16) * 0.05)(B, Hkv, Sk, Dh)),
            "wq": _w((lambda *s: torch.randn(*s, dtype=torch.bfloat16) * 0.8)(D, Hq * Dh) * (D ** -0.5)),
            "wo": _w((lambda *s: torch.randn(*s, dtype=torch.bfloat16) * 0.05)(Hq * Dh, D) * ((Hq * Dh) ** -0.5)),
        }
    _B_in = _B_setup()

    return {
        "A_x": _A_in["x"],
        "A_k_cache": _A_in["k_cache"],
        "A_v_cache": _A_in["v_cache"],
        "A_wq": _A_in["wq"],
        "A_wo": _A_in["wo"],
        "B_x": _B_in["x"],
        "B_k_cache": _B_in["k_cache"],
        "B_v_cache": _B_in["v_cache"],
        "B_wq": _B_in["wq"],
        "B_wo": _B_in["wo"],
    }

def reference(A_x, A_k_cache, A_v_cache, A_wq, A_wo, B_x, B_k_cache, B_v_cache, B_wq, B_wo):
    def _A_ref(x, k_cache, v_cache, wq, wo):
        B, Sq, D = x.shape
        Hq, Dh = 32, 128
        Hkv = k_cache.shape[1]
        rep = Hq // Hkv
        q = (lambda x, *d: x.permute(*d))((x @ wq).reshape(B, Sq, Hq, Dh), 0, 2, 1, 3)
        k = (lambda x, n, axis: torch.repeat_interleave(x, n, dim=axis))(k_cache, rep, axis=1)
        v = (lambda x, n, axis: torch.repeat_interleave(x, n, dim=axis))(v_cache, rep, axis=1)
        scores = torch.einsum("bhqd,bhkd->bhqk", q, k) * (Dh ** -0.5)
        p = _softmax(scores, axis=-1)
        o = torch.einsum("bhqk,bhkd->bhqd", p, v)
        return (lambda x, *d: x.permute(*d))(o, 0, 2, 1, 3).reshape(B, Sq, Hq * Dh) @ wo

    def _B_ref(x, k_cache, v_cache, wq, wo):
        B, Sq, D = x.shape
        Hq, Dh = 32, 128
        Hkv = k_cache.shape[1]
        rep = Hq // Hkv
        q = (lambda x, *d: x.permute(*d))((x @ wq).reshape(B, Sq, Hq, Dh), 0, 2, 1, 3)
        k = (lambda x, n, axis: torch.repeat_interleave(x, n, dim=axis))(k_cache, rep, axis=1)
        v = (lambda x, n, axis: torch.repeat_interleave(x, n, dim=axis))(v_cache, rep, axis=1)
        scores = torch.einsum("bhqd,bhkd->bhqk", q, k) * (Dh ** -0.5)
        p = _softmax(scores, axis=-1)
        o = torch.einsum("bhqk,bhkd->bhqd", p, v)
        return (lambda x, *d: x.permute(*d))(o, 0, 2, 1, 3).reshape(B, Sq, Hq * Dh) @ wo

    a = _A_ref(A_x, A_k_cache, A_v_cache, A_wq, A_wo)
    b = _B_ref(B_x, B_k_cache, B_v_cache, B_wq, B_wo)
    return torch.concatenate([a, b], axis=-1)
```

```cpp
#include <cuda_runtime.h>
#include <cuda_bf16.h>
#include <cuda.h>
#include <stdint.h>

#define CFG_NH 1
#define CFG_D 4
#define CFG_INTERLEAVE 0

namespace {

constexpr int NH   = CFG_NH;
constexpr int G    = 4 * NH;
constexpr int SEG  = NH < 4 ? 4 : NH;
constexpr int TPS  = 16 / SEG;
constexpr int SPH  = SEG / NH;
constexpr int TPH  = 16 / NH;
constexpr int FAN  = 4 * SEG;
constexpr int TILE = 32768;
constexpr int NST  = 6;
constexpr int NTHREADS = 288;
constexpr int NCHUNK = 74;
constexpr int DEPTH = CFG_D;

constexpr int SM_RING = 0;
constexpr int SM_SC   = NST * TILE;
constexpr int SM_Q    = SM_SC + 16384;
constexpr int SM_P    = SM_Q;
constexpr int SM_RED  = SM_P + 8192;
constexpr int SM_OF   = SM_RED + 2048;
constexpr int SM_BAR  = SM_OF + 128;
constexpr int SM_TOTAL = SM_BAR + 256 + 1024;

struct alignas(64) Params {
    CUtensorMap k[2], v[2], wq[2], wo[2];
    const __nv_bfloat16* x[2];
    __nv_bfloat16* out;
};

__device__ uint4  g_q[2 * 16 * 32];
__device__ float4 g_part[128 * FAN * 16];
__device__ float2 g_stat[128 * FAN];
__device__ float4 g_out[2 * 64 * 144];
#define TSTAMP(i) do {} while (0)
#define TANCHOR() do {} while (0)
#define TANCHOR2() do {} while (0)

constexpr uint32_t SPIN_LIMIT = 1u << 24;

__device__ __forceinline__ void mbar_init(uint32_t a, uint32_t c) {
    asm volatile("mbarrier.init.shared::cta.b64 [%0], %1;" ::"r"(a), "r"(c) : "memory");
}
__device__ __forceinline__ void mbar_expect(uint32_t a, uint32_t b) {
    asm volatile("mbarrier.arrive.expect_tx.shared::cta.b64 _, [%0], %1;" ::"r"(a), "r"(b) : "memory");
}
__device__ __forceinline__ void mbar_arrive(uint32_t a) {
    asm volatile("mbarrier.arrive.shared::cta.b64 _, [%0];" ::"r"(a) : "memory");
}
__device__ __forceinline__ void mbar_wait(uint32_t a, uint32_t ph) {
    uint32_t ok, n = 0;
    do {
        asm volatile("{\n .reg .pred p;\n mbarrier.try_wait.parity.shared::cta.b64 p, [%1], %2;\n selp.u32 %0, 1, 0, p;\n}"
                     : "=r"(ok) : "r"(a), "r"(ph) : "memory");
        if (++n > SPIN_LIMIT) __trap();
    } while (!ok);
}
__device__ __forceinline__ void tma2d(uint32_t dst, const CUtensorMap* tm, int c0, int c1, uint32_t mbar, uint64_t pol) {
    asm volatile("cp.async.bulk.tensor.2d.shared::cluster.global.mbarrier::complete_tx::bytes.L2::cache_hint"
                 " [%0], [%1, {%3, %4}], [%2], %5;"
                 ::"r"(dst), "l"(tm), "r"(mbar), "r"(c0), "r"(c1), "l"(pol) : "memory");
}
__device__ __forceinline__ void tma4d(uint32_t dst, const CUtensorMap* tm, int c3, uint32_t mbar, uint64_t pol) {
    asm volatile("cp.async.bulk.tensor.4d.shared::cluster.global.mbarrier::complete_tx::bytes.L2::cache_hint"
                 " [%0], [%1, {%3, %3, %3, %4}], [%2], %5;"
                 ::"r"(dst), "l"(tm), "r"(mbar), "r"(0), "r"(c3), "l"(pol) : "memory");
}
__device__ __forceinline__ void ldsm4(uint32_t (&r)[4], uint32_t a) {
    asm volatile("ldmatrix.sync.aligned.m8n8.x4.shared.b16 {%0,%1,%2,%3}, [%4];"
                 : "=r"(r[0]), "=r"(r[1]), "=r"(r[2]), "=r"(r[3]) : "r"(a) : "memory");
}
__device__ __forceinline__ void ldsm4t(uint32_t (&r)[4], uint32_t a) {
    asm volatile("ldmatrix.sync.aligned.m8n8.x4.trans.shared.b16 {%0,%1,%2,%3}, [%4];"
                 : "=r"(r[0]), "=r"(r[1]), "=r"(r[2]), "=r"(r[3]) : "r"(a) : "memory");
}
__device__ __forceinline__ void mma16816(float (&c)[4], const uint32_t (&a)[4], uint32_t b0, uint32_t b1) {
    asm volatile("mma.sync.aligned.m16n8k16.row.col.f32.bf16.bf16.f32 {%0,%1,%2,%3}, {%4,%5,%6,%7}, {%8,%9}, {%0,%1,%2,%3};"
                 : "+f"(c[0]), "+f"(c[1]), "+f"(c[2]), "+f"(c[3])
                 : "r"(a[0]), "r"(a[1]), "r"(a[2]), "r"(a[3]), "r"(b0), "r"(b1));
}
__device__ __forceinline__ uint4 lds128(uint32_t a) {
    uint4 v;
    asm volatile("ld.shared.v4.u32 {%0,%1,%2,%3}, [%4];" : "=r"(v.x), "=r"(v.y), "=r"(v.z), "=r"(v.w) : "r"(a) : "memory");
    return v;
}
__device__ __forceinline__ void sts128(uint32_t a, uint4 v) {
    asm volatile("st.shared.v4.u32 [%0], {%1,%2,%3,%4};" ::"r"(a), "r"(v.x), "r"(v.y), "r"(v.z), "r"(v.w) : "memory");
}
__device__ __forceinline__ void sts64(uint32_t a, uint32_t x, uint32_t y) {
    asm volatile("st.shared.v2.u32 [%0], {%1,%2};" ::"r"(a), "r"(x), "r"(y) : "memory");
}
__device__ __forceinline__ void sts32(uint32_t a, uint32_t x) {
    asm volatile("st.shared.u32 [%0], %1;" ::"r"(a), "r"(x) : "memory");
}
__device__ __forceinline__ float2 lds64f(uint32_t a) {
    float2 v;
    asm volatile("ld.shared.v2.f32 {%0,%1}, [%2];" : "=f"(v.x), "=f"(v.y) : "r"(a) : "memory");
    return v;
}
__device__ __forceinline__ uint4 ldg_relaxed128(const void* p) {
    uint4 v;
    asm volatile("ld.relaxed.gpu.global.v4.u32 {%0,%1,%2,%3}, [%4];" : "=r"(v.x), "=r"(v.y), "=r"(v.z), "=r"(v.w) : "l"(p) : "memory");
    return v;
}
__device__ __forceinline__ uint2 ldg_relaxed64(const void* p) {
    uint2 v;
    asm volatile("ld.relaxed.gpu.global.v2.u32 {%0,%1}, [%2];" : "=r"(v.x), "=r"(v.y) : "l"(p) : "memory");
    return v;
}
__device__ __forceinline__ void stg_relaxed128(void* p, uint4 v) {
    asm volatile("st.relaxed.gpu.global.v4.u32 [%0], {%1,%2,%3,%4};" ::"l"(p), "r"(v.x), "r"(v.y), "r"(v.z), "r"(v.w) : "memory");
}
__device__ __forceinline__ void stg_relaxed64(void* p, uint32_t x, uint32_t y) {
    asm volatile("st.relaxed.gpu.global.v2.u32 [%0], {%1,%2};" ::"l"(p), "r"(x), "r"(y) : "memory");
}
__device__ __forceinline__ void stg_relaxed32(void* p, uint32_t x) {
    asm volatile("st.relaxed.gpu.global.u32 [%0], %1;" ::"l"(p), "r"(x) : "memory");
}
__device__ __forceinline__ uint32_t nz(float f) {
    uint32_t u = __float_as_uint(f);
    return u == 0u ? 0x80000000u : u;
}
__device__ __forceinline__ bool all_set(const uint4& v) { return v.x != 0u && v.y != 0u && v.z != 0u && v.w != 0u; }
__device__ __forceinline__ uint32_t pack_bf16(float lo, float hi) {
    uint32_t r;
    asm("cvt.rn.bf16x2.f32 %0, %1, %2;" : "=r"(r) : "f"(hi), "f"(lo));
    return r;
}
__device__ __forceinline__ float ex2(float x) {
    float r;
    asm("ex2.approx.ftz.f32 %0, %1;" : "=f"(r) : "f"(x));
    return r;
}
__device__ __forceinline__ float sel4(const float (&c)[4], int j) {
    float a = (j & 1) ? c[1] : c[0];
    float b = (j & 1) ? c[3] : c[2];
    return (j & 2) ? b : a;
}
__device__ __forceinline__ void bar_consumers() { asm volatile("bar.sync 1, 256;" ::: "memory"); }

__global__ void __launch_bounds__(NTHREADS, 1)
gqa2_decode_kernel(const __grid_constant__ Params prm) {
    extern __shared__ unsigned char smem_raw[];
    const uint32_t sb = ((uint32_t)__cvta_generic_to_shared(smem_raw) + 1023u) & ~1023u;
    const int tid = threadIdx.x, warp = tid >> 5, lane = tid & 31;
    const int prob = blockIdx.x >> 6, c = blockIdx.x & 63;
    const int grp = c / G, r = c % G;
    const uint32_t bar_full = sb + SM_BAR, bar_empty = bar_full + 16 * NST;
    const int g8 = lane >> 2, j4 = lane & 3, l8 = lane & 7, m4 = lane >> 3;

    if (warp == 8) {
        if (lane == 0) {
            TANCHOR();
#pragma unroll
            for (int s = 0; s < NST; s++) { mbar_init(bar_full + 16 * s, 1); mbar_init(bar_full + 16 * s + 8, 1); mbar_init(bar_empty + 8 * s, 8); }
            asm volatile("fence.mbarrier_init.release.cluster;" ::: "memory");
        }
        uint64_t pol;
        asm volatile("createpolicy.fractional.L2::evict_first.b64 %0, 1.0;" : "=l"(pol));
        auto item_of = [](int n) { return n < 70 ? n >> 1 : n - 35; };
        auto half_of = [](int n) { return n < 70 ? n & 1 : 0; };
        auto issue = [&](int n) {
            const int it = item_of(n), hf = half_of(n), s = it % NST;
            const uint32_t dst = sb + SM_RING + s * TILE, bar = bar_full + 16 * s + 8 * hf;
            if (n < 6) {
                mbar_expect(bar, 12288);
                tma2d(dst + hf * 12288, &prm.wq[prob], c * 64, n * 96, bar, pol);
            } else if (n < 70) {
                const int i = it - 3, ii = i & 15, hh = ii / TPH, tt = ii % TPH;
                const int kb = CFG_INTERLEAVE ? tt * G + r : r * TPH + tt;
                mbar_expect(bar, TILE / 2);
                tma4d(dst + hf * (TILE / 2), i < 16 ? &prm.k[prob] : &prm.v[prob], (grp * NH + hh) * 1024 + kb * 16 + hf * 8, bar, pol);
            } else {
                mbar_expect(bar, 18432);
                tma2d(dst, &prm.wo[prob], 0, (c * 64 + (n - 70) * 16) * 9, bar, pol);
            }
        };
        if (lane == 0) {
#pragma unroll
            for (int n = 0; n < DEPTH; n++) issue(n);
        }
        __syncthreads();
        if (lane == 0) {
#pragma unroll 1
            for (int n = DEPTH; n < NCHUNK; n++) {
                const int it = item_of(n), pit = item_of(n - DEPTH);
                if (it >= NST && half_of(n) == 0) mbar_wait(bar_empty + 8 * (it % NST), (it / NST - 1) & 1);
                mbar_wait(bar_full + 16 * (pit % NST) + 8 * half_of(n - DEPTH), (pit / NST) & 1);
                issue(n);
                if (n == 69 + DEPTH) TSTAMP(17);
            }
        }
        __syncwarp();
    } else {
        uint32_t xb[3][12];
        {
            const uint32_t* xw = reinterpret_cast<const uint32_t*>(prm.x[prob]) + (warp >> 2) * 48 + j4;
#pragma unroll
            for (int b = 0; b < 3; b++)
#pragma unroll
                for (int t = 0; t < 12; t++) xb[b][t] = __ldg(xw + b * 96 + 4 * t);
        }
        __syncthreads();

        {
            float c0[4] = {0.f, 0.f, 0.f, 0.f}, c1[4] = {0.f, 0.f, 0.f, 0.f};
            const uint32_t base = sb + SM_RING + ((warp >> 2) * 96 + (m4 >> 1) * 8 + l8) * 128 + (((2 * (warp & 3) + (m4 & 1)) ^ l8) << 4);
#pragma unroll
            for (int b = 0; b < 3; b++) {
                mbar_wait(bar_full + 16 * b + 8 * (warp >> 2), 0);
#pragma unroll
                for (int t = 0; t < 3; t++) {
                    uint32_t a0[4], a1[4];
                    ldsm4t(a0, base + b * TILE + (2 * t) * 2048);
                    ldsm4t(a1, base + b * TILE + (2 * t + 1) * 2048);
                    mma16816(c0, a0, xb[b][4 * t], xb[b][4 * t + 1]);
                    mma16816(c1, a1, xb[b][4 * t + 2], xb[b][4 * t + 3]);
                }
                __syncwarp();
                if (lane == 0) mbar_arrive(bar_empty + 8 * b);
            }
            if (j4 < 2) sts32(sb + SM_RED + (warp * 16 + g8 + 8 * j4) * 4, __float_as_uint(j4 ? c0[2] + c1[2] : c0[0] + c1[0]));
        }
        bar_consumers();
        uint32_t* my_q = nullptr;
        if (warp == 0) {
            const float2 va = lds64f(sb + SM_RED + lane * 8), vb = lds64f(sb + SM_RED + 256 + lane * 8);
            uint32_t u = pack_bf16(va.x + vb.x, va.y + vb.y);
            if (u == 0u) u = 0x8000u;
            const int d = 64 * (c & 1) + 2 * lane;
            const int w16 = 2 * (d >> 4) + ((d >> 3) & 1);
            my_q = reinterpret_cast<uint32_t*>(g_q) + (prob * 16 + (c >> 2)) * 128 + (w16 >> 2) * 32 + ((c >> 1) & 1) * 16 + ((d & 7) >> 1) * 4 + (w16 & 3);
            stg_relaxed32(my_q, u);
            TSTAMP(1);
        }
        {
            constexpr int NQ = (NH * 32 + 255) / 256;
            const uint4* src = g_q + (prob * 16 + grp * NH) * 32 + tid;
            if (tid < NH * 32) {
                uint4 v[NQ];
#pragma unroll
                for (int e = 0; e < NQ; e++) v[e] = ldg_relaxed128(src + e * 256);
                uint32_t n = 0;
                bool ok;
                do {
                    ok = true;
#pragma unroll
                    for (int e = 0; e < NQ; e++)
                        if (!all_set(v[e])) { v[e] = ldg_relaxed128(src + e * 256); ok = false; }
                    if (++n > SPIN_LIMIT) __trap();
                } while (!ok);
#pragma unroll
                for (int e = 0; e < NQ; e++) sts128(sb + SM_Q + (tid + e * 256) * 16, v[e]);
            }
        }
        bar_consumers();
        if (warp == 0) TSTAMP(2);
        const uint32_t frag_off = (g8 & 1) * 64 + j4 * 16;
        int s = 3, ph = 0;

        {
            const uint32_t kbase = sb + SM_RING + (2 * warp + (m4 & 1)) * 2048 + l8 * 128 + (((m4 >> 1) ^ l8) << 4);
            const uint32_t sc_addr = sb + SM_SC + (warp * 32 + (j4 & 1) * 16 + (g8 >> 1) * 4 + (g8 & 1) + (j4 >> 1) * 2) * 4;
            uint4 qb[4];
#pragma unroll 1
            for (int i = 0; i < 16; i++) {
                if (i % TPH == 0) {
#pragma unroll
                    for (int q = 0; q < 4; q++) qb[q] = lds128(sb + SM_Q + (i / TPH) * 512 + q * 128 + frag_off);
                }
                mbar_wait(bar_full + 16 * s + 8 * (warp >> 2), ph);
                float c0[4] = {0.f, 0.f, 0.f, 0.f}, c1[4] = {0.f, 0.f, 0.f, 0.f};
                const uint32_t kb = kbase + s * TILE;
#pragma unroll
                for (int q = 0; q < 4; q++) {
                    uint32_t a0[4], a1[4];
                    ldsm4(a0, (kb ^ (((2 * q) & 3) << 5)) + (q >> 1) * 1024);
                    ldsm4(a1, (kb ^ (((2 * q + 1) & 3) << 5)) + (q >> 1) * 1024);
                    mma16816(c0, a0, qb[q].x, qb[q].y);
                    mma16816(c1, a1, qb[q].z, qb[q].w);
                }
                __syncwarp();
                if (lane == 0) mbar_arrive(bar_empty + 8 * s);
                sts32(sc_addr + i * 1024, __float_as_uint(sel4(c0, j4) + sel4(c1, j4)));
                if (++s == NST) { s = 0; ph ^= 1; }
            }
        }
        bar_consumers();
        if (warp == 0) TSTAMP(3);

        {
            constexpr float SCALE = 0.08838834764831845f * 1.4426950408889634f;
            constexpr int NU = (2 * SEG) / 8;
            float4 sv[NU][TPS];
            float mx[NU], sum[NU];
#pragma unroll
            for (int n = 0; n < NU; n++) {
                const int u = warp + 8 * n, sg = u >> 1, hd = u & 1;
                mx[n] = -INFINITY;
#pragma unroll
                for (int t = 0; t < TPS; t++) {
                    uint4 v = lds128(sb + SM_SC + ((sg * TPS + t) * 256 + g8 * 32 + hd * 16 + j4 * 4) * 4);
                    sv[n][t] = make_float4(__uint_as_float(v.x), __uint_as_float(v.y), __uint_as_float(v.z), __uint_as_float(v.w));
                    mx[n] = fmaxf(mx[n], fmaxf(fmaxf(sv[n][t].x, sv[n][t].y), fmaxf(sv[n][t].z, sv[n][t].w)));
                }
            }
#pragma unroll
            for (int o = 16; o > 0; o >>= 1)
#pragma unroll
                for (int n = 0; n < NU; n++) mx[n] = fmaxf(mx[n], __shfl_xor_sync(0xffffffffu, mx[n], o));
            if (warp == 0) TSTAMP(10);
#pragma unroll
            for (int n = 0; n < NU; n++) {
                const int u = warp + 8 * n, sg = u >> 1, hd = u & 1;
                mx[n] *= SCALE;
                sum[n] = 0.f;
#pragma unroll
                for (int t = 0; t < TPS; t++) {
                    const float p0 = ex2(fmaf(sv[n][t].x, SCALE, -mx[n])), p1 = ex2(fmaf(sv[n][t].y, SCALE, -mx[n]));
                    const float p2 = ex2(fmaf(sv[n][t].z, SCALE, -mx[n])), p3 = ex2(fmaf(sv[n][t].w, SCALE, -mx[n]));
                    sum[n] += (p0 + p1) + (p2 + p3);
                    sts64(sb + SM_P + (sg * TPS + t) * 512 + (g8 >> 1) * 128 + hd * 64 + j4 * 16 + (g8 & 1) * 8,
                          pack_bf16(p0, p1), pack_bf16(p2, p3));
                }
            }
            if (warp == 0) TSTAMP(11);
            bar_consumers();
            if (warp == 0) TSTAMP(12);
#pragma unroll
            for (int o = 16; o > 0; o >>= 1)
#pragma unroll
                for (int n = 0; n < NU; n++) sum[n] += __shfl_xor_sync(0xffffffffu, sum[n], o);
#pragma unroll
            for (int n = 0; n < NU; n++) {
                const int u = warp + 8 * n, sg = u >> 1, hd = u & 1;
                if (lane < 2) {
                    const int gk = grp * NH + sg / SPH;
                    stg_relaxed64(&g_stat[(prob * 64 + 4 * gk + 2 * hd + lane) * FAN + r * SPH + sg % SPH], nz(mx[n]), nz(sum[n]));
                }
            }
        }
        if (warp == 0) TSTAMP(4);

        constexpr int NL = FAN / 16;
        float4* const psrc = g_part + (size_t)blockIdx.x * FAN * 16 + tid;
        float2* const st = g_stat + blockIdx.x * FAN;
        uint4 pv[NL];
        float wA = 0.f, wB = 0.f;
        {
            const uint32_t vbase = sb + SM_RING + (m4 >> 1) * 2048 + (warp >> 2) * 1024 + l8 * 128 + (((2 * (warp & 3) + (m4 & 1)) ^ l8) << 4);
            float c0[4] = {0.f, 0.f, 0.f, 0.f}, c1[4] = {0.f, 0.f, 0.f, 0.f};
            auto vtile = [&](int i) {
                uint4 pb[4];
#pragma unroll
                for (int q = 0; q < 4; q++) pb[q] = lds128(sb + SM_P + i * 512 + q * 128 + frag_off);
                const uint32_t vb = vbase + s * TILE;
#pragma unroll
                for (int q = 0; q < 4; q++) {
                    uint32_t a0[4], a1[4];
                    if ((q & 1) == 0) mbar_wait(bar_full + 16 * s + 4 * q, ph);
                    ldsm4t(a0, vb + (2 * q) * 4096);
                    ldsm4t(a1, vb + (2 * q + 1) * 4096);
                    mma16816(c0, a0, pb[q].x, pb[q].y);
                    mma16816(c1, a1, pb[q].z, pb[q].w);
                }
                __syncwarp();
                if (lane == 0) mbar_arrive(bar_empty + 8 * s);
                if (i % TPS == TPS - 1) {
                    const int sg = i / TPS, gk = grp * NH + sg / SPH;
                    float* dst = reinterpret_cast<float*>(g_part) +
                                 ((size_t)(prob * 64 + 4 * gk + 2 * (j4 & 1) + (warp >> 2)) * FAN + r * SPH + sg % SPH) * 64 +
                                 16 * (warp & 3) + g8 + 8 * (j4 >> 1);
                    stg_relaxed32(dst, nz(sel4(c0, j4) + sel4(c1, j4)));
#pragma unroll
                    for (int e = 0; e < 4; e++) { c0[e] = 0.f; c1[e] = 0.f; }
                }
                if (++s == NST) { s = 0; ph ^= 1; }
            };
#pragma unroll 1
            for (int i = 0; i < 15; i++) vtile(i);
            if (warp == 0) TSTAMP(13);
            {
                uint2 sa = make_uint2(0xff800000u, 0x80000000u), sbb = sa;
                if (lane < FAN) sa = ldg_relaxed64(st + lane);
                if (FAN > 32) sbb = ldg_relaxed64(st + 32 + lane);
#pragma unroll
                for (int i = 0; i < NL; i++) pv[i] = ldg_relaxed128(psrc + i * 256);
                uint32_t n = 0;
                while (sa.x == 0u || sa.y == 0u) { sa = ldg_relaxed64(st + lane); if (++n > SPIN_LIMIT) __trap(); }
                while (sbb.x == 0u || sbb.y == 0u) { sbb = ldg_relaxed64(st + 32 + lane); if (++n > SPIN_LIMIT) __trap(); }
                __syncwarp();
                const float mA = __uint_as_float(sa.x), mB = __uint_as_float(sbb.x);
                float M = fmaxf(mA, mB);
#pragma unroll
                for (int o = 16; o > 0; o >>= 1) M = fmaxf(M, __shfl_xor_sync(0xffffffffu, M, o));
                wA = ex2(mA - M); wB = ex2(mB - M);
                float L = wA * __uint_as_float(sa.y) + wB * __uint_as_float(sbb.y);
#pragma unroll
                for (int o = 16; o > 0; o >>= 1) L += __shfl_xor_sync(0xffffffffu, L, o);
                const float inv = 1.0f / L;
                wA *= inv; wB *= inv;
            }
            if (warp == 0) TSTAMP(14);
            vtile(15);
        }
        if (warp == 0) TSTAMP(5);

        {
            uint32_t n = 0;
            bool ok;
            do {
                ok = true;
#pragma unroll
                for (int i = 0; i < NL; i++)
                    if (!all_set(pv[i])) { pv[i] = ldg_relaxed128(psrc + i * 256); ok = false; }
                if (++n > SPIN_LIMIT) __trap();
            } while (!ok);
            __syncwarp();
            if (warp == 0) TSTAMP(15);
            float4 acc = make_float4(0.f, 0.f, 0.f, 0.f);
#pragma unroll
            for (int i = 0; i < NL; i++) {
                const int f = 2 * warp + (lane >> 4) + 16 * i;
                const float w = __shfl_sync(0xffffffffu, i < 2 ? wA : wB, f & 31);
                acc.x = fmaf(w, __uint_as_float(pv[i].x), acc.x);
                acc.y = fmaf(w, __uint_as_float(pv[i].y), acc.y);
                acc.z = fmaf(w, __uint_as_float(pv[i].z), acc.z);
                acc.w = fmaf(w, __uint_as_float(pv[i].w), acc.w);
            }
            acc.x += __shfl_xor_sync(0xffffffffu, acc.x, 16);
            acc.y += __shfl_xor_sync(0xffffffffu, acc.y, 16);
            acc.z += __shfl_xor_sync(0xffffffffu, acc.z, 16);
            acc.w += __shfl_xor_sync(0xffffffffu, acc.w, 16);
            if (lane < 16)
                sts128(sb + SM_RED + (warp * 64 + lane * 4) * 4,
                       make_uint4(__float_as_uint(acc.x), __float_as_uint(acc.y), __float_as_uint(acc.z), __float_as_uint(acc.w)));
            bar_consumers();
            if (warp == 0) TSTAMP(16);
            if (warp == 0) {
                float s0 = 0.f, s1 = 0.f;
#pragma unroll
                for (int w = 0; w < 8; w++) { float2 v = lds64f(sb + SM_RED + (w * 64 + 2 * lane) * 4); s0 += v.x; s1 += v.y; }
                sts32(sb + SM_OF + (j4 * 8 + (lane >> 2)) * 4, pack_bf16(s0, s1));
                stg_relaxed32(my_q, 0u);
                if (lane < FAN) stg_relaxed64(st + lane, 0u, 0u);
                if (FAN > 32) stg_relaxed64(st + 32 + lane, 0u, 0u);
            }
#pragma unroll
            for (int i = 0; i < NL; i++) stg_relaxed128(psrc + i * 256, make_uint4(0u, 0u, 0u, 0u));
        }
    }
    __syncthreads();
    if (warp == 0) TSTAMP(6);

    {
        const uint4 o0 = lds128(sb + SM_OF + j4 * 32), o1 = lds128(sb + SM_OF + j4 * 32 + 16);
        const uint32_t ob[8] = {o0.x, o0.y, o0.z, o0.w, o1.x, o1.y, o1.z, o1.w};
        float acc[4][4];
#pragma unroll
        for (int mt = 0; mt < 4; mt++) { acc[mt][0] = acc[mt][1] = acc[mt][2] = acc[mt][3] = 0.f; }
        const int rho = 9 * ((m4 >> 1) * 8 + l8) + warp;
        const uint32_t base = sb + SM_RING + rho * 128 + (((m4 & 1) ^ (rho & 7)) << 4);
#pragma unroll
        for (int t = 0; t < 4; t++) {
            mbar_wait(bar_full + 16 * ((35 + t) % NST), ((35 + t) / NST) & 1);
            if (t == 3 && warp == 0) TSTAMP(9);
#pragma unroll
            for (int mt = 0; mt < 4; mt++) {
                uint32_t a[4];
                ldsm4t(a, (base ^ (mt << 5)) + ((35 + t) % NST) * TILE);
                mma16816(acc[mt], a, ob[2 * t], ob[2 * t + 1]);
            }
        }
        const float v0 = j4 == 0 ? acc[0][0] : j4 == 1 ? acc[1][0] : j4 == 2 ? acc[2][0] : acc[3][0];
        const float v1 = j4 == 0 ? acc[0][2] : j4 == 1 ? acc[1][2] : j4 == 2 ? acc[2][2] : acc[3][2];
        stg_relaxed64(reinterpret_cast<float*>(g_out) + (size_t)blockIdx.x * 576 + warp * 64 + 16 * j4 + 2 * g8, nz(v0), nz(v1));
    }
    if (warp == 0) TSTAMP(7);

    const int u = warp * 64 + c;
    if (u < 144) {
        float4* src = g_out + (size_t)(prob * 64 + lane) * 144 + u;
        uint4 a = ldg_relaxed128(src), b = ldg_relaxed128(src + 32 * 144);
        uint32_t n = 0;
        while (!(all_set(a) && all_set(b))) {
            if (!all_set(a)) a = ldg_relaxed128(src);
            if (!all_set(b)) b = ldg_relaxed128(src + 32 * 144);
            if (++n > SPIN_LIMIT) __trap();
        }
        __syncwarp();
        if (warp == 0) TSTAMP(19);
        const float x = __uint_as_float(a.x) + __uint_as_float(b.x), y = __uint_as_float(a.y) + __uint_as_float(b.y);
        const float z = __uint_as_float(a.z) + __uint_as_float(b.z), w = __uint_as_float(a.w) + __uint_as_float(b.w);
        const bool up = lane >= 16;
        float k0 = (up ? y : x) + __shfl_xor_sync(0xffffffffu, up ? x : y, 16);
        float k1 = (up ? w : z) + __shfl_xor_sync(0xffffffffu, up ? z : w, 16);
#pragma unroll
        for (int o = 8; o > 0; o >>= 1) {
            k0 += __shfl_xor_sync(0xffffffffu, k0, o);
            k1 += __shfl_xor_sync(0xffffffffu, k1, o);
        }
        if ((lane & 15) == 0) {
            const int cb = 16 * (u >> 2) + 2 * (u & 3) + (up ? 8 : 0);
            *reinterpret_cast<uint32_t*>(prm.out + prob * 576 + cb) = pack_bf16(k0, k1);
        }
        stg_relaxed128(src, make_uint4(0u, 0u, 0u, 0u));
        stg_relaxed128(src + 32 * 144, make_uint4(0u, 0u, 0u, 0u));
        if (warp == 0) { TSTAMP(8); TANCHOR2(); }
    }
}

typedef CUresult (*EncodeFn)(CUtensorMap*, CUtensorMapDataType, cuuint32_t, void*, const cuuint64_t*, const cuuint64_t*,
                             const cuuint32_t*, const cuuint32_t*, CUtensorMapInterleave, CUtensorMapSwizzle,
                             CUtensorMapL2promotion, CUtensorMapFloatOOBfill);

}

extern "C" void kernel_launch(void* const* d_in, const int* in_sizes, int n_in, void* d_out, int out_size) {
    (void)in_sizes; (void)n_in; (void)out_size;
    static EncodeFn enc = nullptr;
    if (!enc) {
        cudaDriverEntryPointQueryResult qr;
        void* fn = nullptr;
        cudaGetDriverEntryPoint("cuTensorMapEncodeTiled", &fn, cudaEnableDefault, &qr);
        enc = (EncodeFn)fn;
        cudaFuncSetAttribute(gqa2_decode_kernel, cudaFuncAttributeMaxDynamicSharedMemorySize, SM_TOTAL);
    }
    Params prm;
    const cuuint32_t es[4] = {1, 1, 1, 1};
    for (int p = 0; p < 2; p++) {
        void* x = d_in[5 * p + 0];
        void* kv[2] = {d_in[5 * p + 1], d_in[5 * p + 2]};
        void* wq = d_in[5 * p + 3];
        void* wo = d_in[5 * p + 4];
        prm.x[p] = (const __nv_bfloat16*)x;
        for (int i = 0; i < 2; i++) {
            const cuuint64_t gd[4] = {64, 8, 2, 16 * 8192 / 8};
            const cuuint64_t gs[3] = {256, 128, 2048};
            const cuuint32_t bd[4] = {64, 8, 2, 8};
            enc(i == 0 ? &prm.k[p] : &prm.v[p], CU_TENSOR_MAP_DATA_TYPE_BFLOAT16, 4, kv[i], gd, gs, bd, es,
                CU_TENSOR_MAP_INTERLEAVE_NONE, CU_TENSOR_MAP_SWIZZLE_128B, CU_TENSOR_MAP_L2_PROMOTION_L2_128B,
                CU_TENSOR_MAP_FLOAT_OOB_FILL_NONE);
        }
        {
            const cuuint64_t gd[2] = {4096, 576};
            const cuuint64_t gs[1] = {8192};
            const cuuint32_t bd[2] = {64, 96};
            enc(&prm.wq[p], CU_TENSOR_MAP_DATA_TYPE_BFLOAT16, 2, wq, gd, gs, bd, es, CU_TENSOR_MAP_INTERLEAVE_NONE,
                CU_TENSOR_MAP_SWIZZLE_128B, CU_TENSOR_MAP_L2_PROMOTION_L2_128B, CU_TENSOR_MAP_FLOAT_OOB_FILL_NONE);
        }
        {
            const cuuint64_t gd[2] = {64, 4096 * 9};
            const cuuint64_t gs[1] = {128};
            const cuuint32_t bd[2] = {64, 144};
            enc(&prm.wo[p], CU_TENSOR_MAP_DATA_TYPE_BFLOAT16, 2, wo, gd, gs, bd, es, CU_TENSOR_MAP_INTERLEAVE_NONE,
                CU_TENSOR_MAP_SWIZZLE_128B, CU_TENSOR_MAP_L2_PROMOTION_L2_128B, CU_TENSOR_MAP_FLOAT_OOB_FILL_NONE);
        }
    }
    prm.out = (__nv_bfloat16*)d_out;
    gqa2_decode_kernel<<<128, NTHREADS, SM_TOTAL>>>(prm);
}
```

```cpp
#include <cuda_runtime.h>
#include <cuda_bf16.h>
#include <cuda.h>
#include <stdint.h>

namespace {

constexpr int TILE = 32768;
constexpr int NST  = 6;
constexpr int DEPTH = 4;
constexpr int NTHREADS = 416;

constexpr int SM_RING = 0;
constexpr int SM_SC   = NST * TILE;
constexpr int SM_P    = SM_SC + 16384;
constexpr int SM_Q    = SM_P;
constexpr int SM_X    = SM_P + 8192;
constexpr int SM_RED  = SM_X + 1152;
constexpr int SM_OF   = SM_RED + 512;
constexpr int SM_PROG = SM_OF + 128;
constexpr int SM_BAR  = SM_PROG + 16;
constexpr int SM_TOTAL = SM_BAR + 256 + 1024;

struct alignas(64) Params {
    CUtensorMap tm[2][4];
    const __nv_bfloat16* x[2];
    __nv_bfloat16* out;
};

struct alignas(4096) Scratch {
    float4 out[128 * 144];
    float4 part[128 * 256];
    uint4  q[128 * 8];
    float4 stat[8 * 64];
    unsigned int cnt[3 * 32];
};
__device__ Scratch g_s;

constexpr uint32_t SPIN_LIMIT = 1u << 24;

__device__ __forceinline__ void mbar_init(uint32_t a, uint32_t c) {
    asm volatile("mbarrier.init.shared::cta.b64 [%0], %1;" ::"r"(a), "r"(c) : "memory");
}
__device__ __forceinline__ void mbar_expect(uint32_t a, uint32_t b) {
    asm volatile("mbarrier.arrive.expect_tx.shared::cta.b64 _, [%0], %1;" ::"r"(a), "r"(b) : "memory");
}
__device__ __forceinline__ void mbar_arrive(uint32_t a) {
    asm volatile("mbarrier.arrive.shared::cta.b64 _, [%0];" ::"r"(a) : "memory");
}
__device__ __forceinline__ void mbar_wait(uint32_t a, uint32_t ph) {
    uint32_t ok, n = 0;
    do {
        asm volatile("{\n .reg .pred p;\n mbarrier.try_wait.parity.shared::cta.b64 p, [%1], %2;\n selp.u32 %0, 1, 0, p;\n}"
                     : "=r"(ok) : "r"(a), "r"(ph) : "memory");
        if (++n > SPIN_LIMIT) __trap();
    } while (!ok);
}
__device__ __forceinline__ bool mbar_test(uint32_t a, uint32_t ph) {
    uint32_t ok;
    asm volatile("{\n .reg .pred p;\n mbarrier.test_wait.parity.shared::cta.b64 p, [%1], %2;\n selp.u32 %0, 1, 0, p;\n}"
                 : "=r"(ok) : "r"(a), "r"(ph) : "memory");
    return __all_sync(0xffffffffu, ok != 0);
}
__device__ __forceinline__ void tma4d(uint32_t dst, const CUtensorMap* tm, int c0, int c1, int c3, uint32_t mbar, uint64_t pol) {
    asm volatile("cp.async.bulk.tensor.4d.shared::cluster.global.mbarrier::complete_tx::bytes.L2::cache_hint"
                 " [%0], [%1, {%3, %4, %5, %6}], [%2], %7;"
                 ::"r"(dst), "l"(tm), "r"(mbar), "r"(c0), "r"(c1), "r"(0), "r"(c3), "l"(pol) : "memory");
}
__device__ __forceinline__ void ldsm4(uint32_t (&r)[4], uint32_t a) {
    asm volatile("ldmatrix.sync.aligned.m8n8.x4.shared.b16 {%0,%1,%2,%3}, [%4];"
                 : "=r"(r[0]), "=r"(r[1]), "=r"(r[2]), "=r"(r[3]) : "r"(a) : "memory");
}
__device__ __forceinline__ void ldsm4t(uint32_t (&r)[4], uint32_t a) {
    asm volatile("ldmatrix.sync.aligned.m8n8.x4.trans.shared.b16 {%0,%1,%2,%3}, [%4];"
                 : "=r"(r[0]), "=r"(r[1]), "=r"(r[2]), "=r"(r[3]) : "r"(a) : "memory");
}
__device__ __forceinline__ void mma16816(float (&c)[4], const uint32_t (&a)[4], uint32_t b0, uint32_t b1) {
    asm volatile("mma.sync.aligned.m16n8k16.row.col.f32.bf16.bf16.f32 {%0,%1,%2,%3}, {%4,%5,%6,%7}, {%8,%9}, {%0,%1,%2,%3};"
                 : "+f"(c[0]), "+f"(c[1]), "+f"(c[2]), "+f"(c[3])
                 : "r"(a[0]), "r"(a[1]), "r"(a[2]), "r"(a[3]), "r"(b0), "r"(b1));
}
__device__ __forceinline__ uint4 lds128(uint32_t a) {
    uint4 v;
    asm volatile("ld.shared.v4.u32 {%0,%1,%2,%3}, [%4];" : "=r"(v.x), "=r"(v.y), "=r"(v.z), "=r"(v.w) : "r"(a) : "memory");
    return v;
}
__device__ __forceinline__ float4 lds128f(uint32_t a) {
    float4 v;
    asm volatile("ld.shared.v4.f32 {%0,%1,%2,%3}, [%4];" : "=f"(v.x), "=f"(v.y), "=f"(v.z), "=f"(v.w) : "r"(a) : "memory");
    return v;
}
__device__ __forceinline__ float2 lds64f(uint32_t a) {
    float2 v;
    asm volatile("ld.shared.v2.f32 {%0,%1}, [%2];" : "=f"(v.x), "=f"(v.y) : "r"(a) : "memory");
    return v;
}
__device__ __forceinline__ uint32_t lds32v(uint32_t a) {
    uint32_t v;
    asm volatile("ld.volatile.shared.u32 %0, [%1];" : "=r"(v) : "r"(a) : "memory");
    return v;
}
__device__ __forceinline__ void sts128(uint32_t a, uint4 v) {
    asm volatile("st.shared.v4.u32 [%0], {%1,%2,%3,%4};" ::"r"(a), "r"(v.x), "r"(v.y), "r"(v.z), "r"(v.w) : "memory");
}
__device__ __forceinline__ void sts64(uint32_t a, uint32_t x, uint32_t y) {
    asm volatile("st.shared.v2.u32 [%0], {%1,%2};" ::"r"(a), "r"(x), "r"(y) : "memory");
}
__device__ __forceinline__ void sts32(uint32_t a, uint32_t x) {
    asm volatile("st.volatile.shared.u32 [%0], %1;" ::"r"(a), "r"(x) : "memory");
}
__device__ __forceinline__ void poll128(uint4& v, const void* p, bool pred) {
    asm volatile("{\n .reg .pred p;\n setp.ne.u32 p, %5, 0;\n @p ld.relaxed.gpu.global.v4.u32 {%0,%1,%2,%3}, [%4];\n}"
                 : "+r"(v.x), "+r"(v.y), "+r"(v.z), "+r"(v.w) : "l"(p), "r"((uint32_t)pred) : "memory");
}
__device__ __forceinline__ void stg128(void* p, uint4 v) {
    asm volatile("st.relaxed.gpu.global.v4.u32 [%0], {%1,%2,%3,%4};" ::"l"(p), "r"(v.x), "r"(v.y), "r"(v.z), "r"(v.w) : "memory");
}
__device__ __forceinline__ void stg64(void* p, uint32_t x, uint32_t y) {
    asm volatile("st.relaxed.gpu.global.v2.u32 [%0], {%1,%2};" ::"l"(p), "r"(x), "r"(y) : "memory");
}
__device__ __forceinline__ void stg32(void* p, uint32_t x) {
    asm volatile("st.relaxed.gpu.global.u32 [%0], %1;" ::"l"(p), "r"(x) : "memory");
}
__device__ __forceinline__ uint32_t nz(float f) {
    uint32_t u = __float_as_uint(f);
    return u == 0u ? 0x80000000u : u;
}
__device__ __forceinline__ bool all_set(const uint4& v) { return v.x != 0u && v.y != 0u && v.z != 0u && v.w != 0u; }
__device__ __forceinline__ void poll2(uint4& a, const void* pa, uint4& b, const void* pb, int sleep_ns) {
    uint32_t n = 0;
    while (true) {
        const bool ma = !all_set(a), mb = !all_set(b);
        if (!__any_sync(0xffffffffu, ma || mb)) break;
        if (sleep_ns && n) __nanosleep(sleep_ns);
        poll128(a, pa, ma);
        poll128(b, pb, mb);
        if (++n > SPIN_LIMIT) __trap();
    }
}
__device__ __forceinline__ uint32_t pack_bf16(float lo, float hi) {
    uint32_t r;
    asm("cvt.rn.bf16x2.f32 %0, %1, %2;" : "=r"(r) : "f"(hi), "f"(lo));
    return r;
}
__device__ __forceinline__ float ex2(float x) {
    float r;
    asm("ex2.approx.ftz.f32 %0, %1;" : "=f"(r) : "f"(x));
    return r;
}
__device__ __forceinline__ float sel4(const float (&c)[4], int j) {
    float a = (j & 1) ? c[1] : c[0];
    float b = (j & 1) ? c[3] : c[2];
    return (j & 2) ? b : a;
}
__device__ __forceinline__ bool elect_one() {
    uint32_t p;
    asm volatile("{\n .reg .pred p;\n elect.sync _|p, 0xffffffff;\n selp.u32 %0, 1, 0, p;\n}" : "=r"(p));
    return p != 0;
}
__device__ __forceinline__ void bar_consumers() { asm volatile("bar.sync 1, 256;" ::: "memory"); }

__global__ void __launch_bounds__(NTHREADS, 1)
gqa2_decode_kernel(const __grid_constant__ Params prm) {
    extern __shared__ unsigned char smem_raw[];
    const uint32_t sb = ((uint32_t)__cvta_generic_to_shared(smem_raw) + 1023u) & ~1023u;
    const int tid = threadIdx.x, warp = tid >> 5, lane = tid & 31;
    const int bid = blockIdx.x, prob = bid >> 6, c = bid & 63;
    const uint32_t bar_full = sb + SM_BAR, bar_wo = bar_full + 16 * NST, bar_empty = bar_wo + 32;
    const uint32_t bar_ready = bar_empty + 8 * NST, bar_x = bar_ready + 8, bar_of = bar_ready + 16,
                   bar_go = bar_ready + 24, bar_ofa = bar_ready + 56;

    int wu = __shfl_sync(0xffffffffu, warp, 0);
    if (wu == 8) {
        uint64_t pol;
        asm volatile("createpolicy.fractional.L2::evict_first.b64 %0, 1.0;" : "=l"(pol));
        if (elect_one()) {
#pragma unroll
            for (int s = 0; s < 2 * NST; s++) mbar_init(bar_full + 8 * s, 1);
            asm volatile("fence.mbarrier_init.release.cluster;" ::: "memory");
#pragma unroll
            for (int n = 0; n < DEPTH; n++) {
                mbar_expect(bar_full + 8 * n, 12288);
                tma4d(sb + SM_RING + (n >> 1) * TILE + (n & 1) * 12288, &prm.tm[prob][0], c * 64, n * 96, 0, bar_full + 8 * n, pol);
            }
#pragma unroll
            for (int s = 0; s < 4; s++) mbar_init(bar_wo + 8 * s, 1);
#pragma unroll
            for (int s = 0; s < NST; s++) mbar_init(bar_empty + 8 * s, 8);
#pragma unroll
            for (int s = 0; s < 7; s++) mbar_init(bar_ready + 8 * s, 1);
            mbar_init(bar_ofa, 3);
            asm volatile("fence.mbarrier_init.release.cluster;" ::: "memory");
            mbar_expect(bar_x, 1152);
            asm volatile("cp.async.bulk.shared::cluster.global.mbarrier::complete_tx::bytes [%0], [%1], 1152, [%2];"
                         ::"r"(sb + SM_X), "l"(prm.x[prob]), "r"(bar_x) : "memory");
            sts64(sb + SM_PROG, 0u, 0u);
#pragma unroll
            for (int k = 1; k < 4; k++) asm volatile("prefetch.tensormap [%0];" ::"l"(&prm.tm[prob][k]) : "memory");
        }
        __syncwarp();
        asm volatile("bar.arrive 3, %0;" ::"n"(NTHREADS) : "memory");
        int ib = DEPTH, iph = 0;
        int nw = 0, wb = 0, wph = 0;
#pragma unroll 1
        for (int n = DEPTH; n < 70; n++) {
            const bool kv = n >= 6;
            const int bytes = kv ? TILE / 2 : 12288;
            const uint32_t dst = sb + SM_RING + (ib >> 1) * TILE + (ib & 1) * bytes, bar = bar_full + 8 * ib;
            if (n >= 2 * NST && (n & 1) == 0) mbar_wait(bar_empty + 4 * ib, iph ^ 1);
            if (elect_one()) mbar_expect(bar, bytes);
            while (true) {
                int win = DEPTH;
                if (n >= 10) {
                    const int lag = (int)(lds32v(sb + SM_PROG) & 8191u) - ((n - 6) * 128 - 192);
                    win = min(max(DEPTH + (lag >> 7), 2), 8);
                }
                if (n - nw < win) break;
                mbar_wait(bar_full + 8 * wb, wph);
                nw++;
                if (++wb == 2 * NST) { wb = 0; wph ^= 1; }
            }
            if (elect_one()) {
                tma4d(dst, &prm.tm[prob][kv + (n >= 38)], kv ? 0 : c * 64, kv ? 0 : n * 96, kv ? (((n - 6) & 31) >> 3) * 4096 + c * 64 + ((n - 6) & 7) * 8 : 0, bar, pol);
                if (kv) asm volatile("red.relaxed.gpu.global.add.u32 [%0], 1;" ::"l"(g_s.cnt + 64) : "memory");
            }
            if (++ib == 2 * NST) { ib = 0; iph ^= 1; }
        }
        if (elect_one()) sts32(sb + SM_PROG + 4, 1u);
#pragma unroll
        for (int k = 0; k < 4; k++) {
            if (k == 0) mbar_wait(bar_empty + 40, 0);
            else if (k < 3) mbar_wait(bar_empty + 8 * (k - 1), 1);
            mbar_wait(bar_full + 8 * ((70 + k - DEPTH) % 12), ((70 + k - DEPTH) / 12) & 1);
            if (elect_one())
                tma4d(sb + SM_RING + (k ? (k - 1) * 18432 : 5 * TILE), &prm.tm[prob][3], 0, (k * 1024 + c * 16) * 9, 0, bar_wo + 8 * k, pol);
        }
    } else {
        asm volatile("bar.sync 3, %0;" ::"n"(NTHREADS) : "memory");
    }
    asm volatile("" : "+r"(wu));
    const int g8 = lane >> 2, j4 = lane & 3, l8 = lane & 7, m4 = lane >> 3;
    const uint4 zero4 = make_uint4(0u, 0u, 0u, 0u);

    if (wu == 9) {
        float4* const psrc = g_s.part + bid * 256 + lane;
#pragma unroll
        for (int i = 0; i < 8; i++) stg128(psrc + 32 * i, zero4);
#pragma unroll
        for (int i = 0; i < 4; i++) stg128(g_s.out + bid * 144 + i * 32 + lane, zero4);
        if (lane < 16) stg128(g_s.out + bid * 144 + 128 + lane, zero4);
        else if (lane < 20) stg128(g_s.stat + bid * 4 + (lane - 16), zero4);
        __syncwarp();
        if (lane == 0) {
            unsigned int v, n = 0;
            asm volatile("atom.release.gpu.global.add.u32 %0, [%1], 1;" : "=r"(v) : "l"(g_s.cnt + prob * 32) : "memory");
            const unsigned int target = (v & ~63u) + 64u;
            do {
                __nanosleep(500);
                asm volatile("ld.relaxed.gpu.global.u32 %0, [%1];" : "=r"(v) : "l"(g_s.cnt + prob * 32) : "memory");
                if (++n > SPIN_LIMIT) __trap();
            } while ((int)(v - target) < 0);
            asm volatile("ld.acquire.gpu.global.u32 %0, [%1];" : "=r"(v) : "l"(g_s.cnt + prob * 32) : "memory");
            mbar_arrive(bar_ready);
        }
        __syncwarp();
        mbar_wait(bar_go, 0);
        float e0, e1;
        {
            uint4 sa = zero4, dummy = make_uint4(1u, 1u, 1u, 1u);
            poll2(sa, g_s.stat + (bid >> 3) * 32 + lane, dummy, g_s.stat, 300);
            if (lane < 8) stg128(g_s.q + (prob * 16 + ((c >> 2) & 3) * 4 + (c >> 4)) * 32 + (c & 3) * 8 + lane, zero4);
            const float m0 = __uint_as_float(sa.x), m1 = __uint_as_float(sa.z);
            float M = fmaxf(m0, m1);
#pragma unroll
            for (int o = 4; o > 0; o >>= 1) M = fmaxf(M, __shfl_xor_sync(0xffffffffu, M, o));
            e0 = ex2(m0 - M); e1 = ex2(m1 - M);
            float L = e0 * __uint_as_float(sa.y) + e1 * __uint_as_float(sa.w);
#pragma unroll
            for (int o = 4; o > 0; o >>= 1) L += __shfl_xor_sync(0xffffffffu, L, o);
            const float inv = 1.0f / L;
            e0 *= inv; e1 *= inv;
        }
        const bool up = lane >= 16;
        const int pr = 2 * j4 + (up ? 1 : 0);
        const uint32_t of_addr = sb + SM_OF + ((pr & 3) * 8 + (pr >> 2)) * 4;
#pragma unroll 1
        for (int t = 0; t < 4; t++) {
            const float a0 = __shfl_sync(0xffffffffu, e0, 8 * t + (g8 >> 1)), a1 = __shfl_sync(0xffffffffu, e1, 8 * t + (g8 >> 1));
            const float b0 = __shfl_sync(0xffffffffu, e0, 8 * t + 4 + (g8 >> 1)), b1 = __shfl_sync(0xffffffffu, e1, 8 * t + 4 + (g8 >> 1));
            const float w0 = (g8 & 1) ? a1 : a0, w1 = (g8 & 1) ? b1 : b0;
            mbar_wait(bar_go + 8 * t, 0);
            if (t < 3) __nanosleep(2000);
            uint4 pa = zero4, pb = zero4;
            poll2(pa, psrc + 64 * t, pb, psrc + 64 * t + 32, t < 3 ? 300 : 0);
            const float x = w0 * __uint_as_float(pa.x) + w1 * __uint_as_float(pb.x), y = w0 * __uint_as_float(pa.y) + w1 * __uint_as_float(pb.y);
            const float z = w0 * __uint_as_float(pa.z) + w1 * __uint_as_float(pb.z), w = w0 * __uint_as_float(pa.w) + w1 * __uint_as_float(pb.w);
            float k0 = (up ? z : x) + __shfl_xor_sync(0xffffffffu, up ? x : z, 16);
            float k1 = (up ? w : y) + __shfl_xor_sync(0xffffffffu, up ? y : w, 16);
#pragma unroll
            for (int o = 8; o > 2; o >>= 1) {
                k0 += __shfl_xor_sync(0xffffffffu, k0, o);
                k1 += __shfl_xor_sync(0xffffffffu, k1, o);
            }
            if ((lane & 12) == 0) sts32(of_addr + 8 * t, pack_bf16(k0, k1));
            __syncwarp();
            if (lane == 0) mbar_arrive(t < 3 ? bar_ofa : bar_of);
        }
        return;
    } else if (wu > 9) {
        if (wu == 10 && lane < 4) mbar_expect(bar_wo + 8 * lane, 18432);
        if (wu == 12) {
            uint32_t n = 0;
            while (lds32v(sb + SM_PROG + 4) == 0u && ++n < SPIN_LIMIT) {
                uint32_t v;
                asm volatile("ld.relaxed.gpu.global.u32 %0, [%1];" : "=r"(v) : "l"(g_s.cnt + 64) : "memory");
                if (lane == 0) sts32(sb + SM_PROG, v);
            }
        }
        const int u = (wu - 10) * 64 + c;
        if (u >= 144) return;
        const float4* const osrc = g_s.out + (prob * 64 + lane) * 144 + u;
        const bool up = lane >= 16;
        uint32_t* const optr = reinterpret_cast<uint32_t*>(prm.out + prob * 576 + 16 * (u >> 2) + 2 * (u & 3) + (up ? 8 : 0));
        mbar_wait(bar_of, 0);
        mbar_wait(bar_wo + 16, 0);
        uint4 a = zero4, b = zero4;
        poll2(a, osrc, b, osrc + 32 * 144, 0);
        const float x = __uint_as_float(a.x) + __uint_as_float(b.x), y = __uint_as_float(a.y) + __uint_as_float(b.y);
        const float z = __uint_as_float(a.z) + __uint_as_float(b.z), w = __uint_as_float(a.w) + __uint_as_float(b.w);
        float k0 = (up ? y : x) + __shfl_xor_sync(0xffffffffu, up ? x : y, 16);
        float k1 = (up ? w : z) + __shfl_xor_sync(0xffffffffu, up ? z : w, 16);
#pragma unroll
        for (int o = 8; o > 0; o >>= 1) {
            k0 += __shfl_xor_sync(0xffffffffu, k0, o);
            k1 += __shfl_xor_sync(0xffffffffu, k1, o);
        }
        if ((lane & 15) == 0) *optr = pack_bf16(k0, k1);
        return;
    } else if (wu < 8) {
        {
            uint32_t xb[3][12];
            mbar_wait(bar_x, 0);
#pragma unroll
            for (int b = 0; b < 3; b++)
#pragma unroll
                for (int t = 0; t < 12; t++) xb[b][t] = lds32v(sb + SM_X + ((warp >> 2) * 48 + j4 + b * 96 + 4 * t) * 4);
            float c0[4] = {0.f, 0.f, 0.f, 0.f}, c1[4] = {0.f, 0.f, 0.f, 0.f};
            const uint32_t base = sb + SM_RING + ((warp >> 2) * 96 + (m4 >> 1) * 8 + l8) * 128 + (((2 * (warp & 3) + (m4 & 1)) ^ l8) << 4);
#pragma unroll
            for (int b = 0; b < 3; b++) {
                mbar_wait(bar_full + 16 * b + 8 * (warp >> 2), 0);
#pragma unroll
                for (int t = 0; t < 3; t++) {
                    uint32_t a0[4], a1[4];
                    ldsm4t(a0, base + b * TILE + (2 * t) * 2048);
                    ldsm4t(a1, base + b * TILE + (2 * t + 1) * 2048);
                    mma16816(c0, a0, xb[b][4 * t], xb[b][4 * t + 1]);
                    mma16816(c1, a1, xb[b][4 * t + 2], xb[b][4 * t + 3]);
                }
                __syncwarp();
                if (lane == 0) mbar_arrive(bar_empty + 8 * b);
            }
            if (j4 < 2) sts32(sb + SM_RED + (warp * 16 + g8 + 8 * j4) * 4, __float_as_uint(j4 ? c0[2] + c1[2] : c0[0] + c1[0]));
        }
        bar_consumers();
        if (warp == 0) {
            const float2 va = lds64f(sb + SM_RED + lane * 8), vb = lds64f(sb + SM_RED + 256 + lane * 8);
            uint32_t u = pack_bf16(va.x + vb.x, va.y + vb.y);
            if (u == 0u) u = 0x8000u;
            const int d = 64 * (c & 1) + 2 * lane;
            const int w16 = 2 * (d >> 4) + ((d >> 3) & 1);
            stg32(reinterpret_cast<uint32_t*>(g_s.q) + (bid >> 2) * 128 + (w16 >> 2) * 32 + ((c >> 1) & 1) * 16 + ((d & 7) >> 1) * 4 + (w16 & 3), u);
        }
        if (warp < 4) {
            uint4 v = zero4, dummy = make_uint4(1u, 1u, 1u, 1u);
            poll2(v, g_s.q + (prob * 16 + warp * 4 + (c >> 4)) * 32 + lane, dummy, g_s.q, 0);
            sts128(sb + SM_Q + warp * 512 + lane * 16, v);
        }
        bar_consumers();
        const uint32_t frag_off = (g8 & 1) * 64 + j4 * 16;
        int s = 3, ph = 0;

        {
            const uint32_t kbase = sb + SM_RING + (2 * warp + (m4 & 1)) * 2048 + l8 * 128 + (((m4 >> 1) ^ l8) << 4);
            const uint32_t sc_addr = sb + SM_SC + (warp * 32 + (j4 & 1) * 16 + (g8 >> 1) * 4 + (g8 & 1) + (j4 >> 1) * 2) * 4;
            uint4 qb[4];
#pragma unroll 1
            for (int i = 0; i < 16; i++) {
                if ((i & 3) == 0) {
#pragma unroll
                    for (int q = 0; q < 4; q++) qb[q] = lds128(sb + SM_Q + (i >> 2) * 512 + q * 128 + frag_off);
                }
                mbar_wait(bar_full + 16 * s + 8 * (warp >> 2), ph);
                float c0[4] = {0.f, 0.f, 0.f, 0.f}, c1[4] = {0.f, 0.f, 0.f, 0.f};
                const uint32_t kb = kbase + s * TILE;
#pragma unroll
                for (int q = 0; q < 4; q++) {
                    uint32_t a0[4], a1[4];
                    ldsm4(a0, (kb ^ (((2 * q) & 3) << 5)) + (q >> 1) * 1024);
                    ldsm4(a1, (kb ^ (((2 * q + 1) & 3) << 5)) + (q >> 1) * 1024);
                    mma16816(c0, a0, qb[q].x, qb[q].y);
                    mma16816(c1, a1, qb[q].z, qb[q].w);
                }
                __syncwarp();
                if (lane == 0) mbar_arrive(bar_empty + 8 * s);
                sts32(sc_addr + i * 1024, __float_as_uint(sel4(c0, j4) + sel4(c1, j4)));
                if (++s == NST) { s = 0; ph ^= 1; }
            }
        }
        mbar_wait(bar_ready, 0);
        bar_consumers();

        {
            constexpr float SCALE = 0.08838834764831845f * 1.4426950408889634f;
            const int hd = warp & 1, st = warp >> 1;
            float4 sv[4];
            float ms = -INFINITY, sum = 0.f;
#pragma unroll
            for (int t = 0; t < 4; t++) {
                sv[t] = lds128f(sb + SM_SC + ((4 * st + t) * 256 + g8 * 32 + hd * 16 + j4 * 4) * 4);
                ms = fmaxf(ms, fmaxf(fmaxf(sv[t].x, sv[t].y), fmaxf(sv[t].z, sv[t].w)));
            }
#pragma unroll
            for (int o = 16; o > 0; o >>= 1) ms = fmaxf(ms, __shfl_xor_sync(0xffffffffu, ms, o));
            ms *= SCALE;
#pragma unroll
            for (int t = 0; t < 4; t++) {
                const float p0 = ex2(fmaf(sv[t].x, SCALE, -ms)), p1 = ex2(fmaf(sv[t].y, SCALE, -ms));
                const float p2 = ex2(fmaf(sv[t].z, SCALE, -ms)), p3 = ex2(fmaf(sv[t].w, SCALE, -ms));
                sum += (p0 + p1) + (p2 + p3);
                sts64(sb + SM_P + (4 * st + t) * 512 + (g8 >> 1) * 128 + hd * 64 + j4 * 16 + (g8 & 1) * 8, pack_bf16(p0, p1), pack_bf16(p2, p3));
            }
            bar_consumers();
#pragma unroll
            for (int o = 16; o > 0; o >>= 1) sum += __shfl_xor_sync(0xffffffffu, sum, o);
            if (lane == 0) stg64(reinterpret_cast<float2*>(g_s.stat) + (((bid >> 4) * 2 + hd) * 4 + st) * 16 + (c & 15), nz(ms), nz(sum));
        }

        {
            const uint32_t vbase = sb + SM_RING + (m4 >> 1) * 2048 + (warp >> 2) * 1024 + l8 * 128 + (((2 * (warp & 3) + (m4 & 1)) ^ l8) << 4);
            float* dst = reinterpret_cast<float*>(g_s.part) + ((bid & ~15) + 8 * (j4 & 1) + warp) * 1024 + (c & 15) * 16 + g8 + 8 * (j4 >> 1);
            float c0[4] = {0.f, 0.f, 0.f, 0.f}, c1[4] = {0.f, 0.f, 0.f, 0.f};
#pragma unroll 1
            for (int i = 0; i < 16; i++) {
                uint4 pb[4];
#pragma unroll
                for (int q = 0; q < 4; q++) pb[q] = lds128(sb + SM_P + i * 512 + q * 128 + frag_off);
                const uint32_t vb = vbase + s * TILE;
#pragma unroll
                for (int q = 0; q < 4; q++) {
                    uint32_t a0[4], a1[4];
                    if ((q & 1) == 0) mbar_wait(bar_full + 16 * s + 4 * q, ph);
                    ldsm4t(a0, vb + (2 * q) * 4096);
                    ldsm4t(a1, vb + (2 * q + 1) * 4096);
                    mma16816(c0, a0, pb[q].x, pb[q].y);
                    mma16816(c1, a1, pb[q].z, pb[q].w);
                }
                __syncwarp();
                if (lane == 0) mbar_arrive(bar_empty + 8 * s);
                if ((i & 3) == 3) {
                    stg32(dst, nz(sel4(c0, j4) + sel4(c1, j4)));
                    dst += 256;
#pragma unroll
                    for (int e = 0; e < 4; e++) { c0[e] = 0.f; c1[e] = 0.f; }
                    if (tid == 0) mbar_arrive(bar_go + 2 * (i - 3));
                }
                if (++s == NST) { s = 0; ph ^= 1; }
            }
        }
    }

    {
        float acc[2][4][4];
#pragma unroll
        for (int e = 0; e < 32; e++) (&acc[0][0][0])[e] = 0.f;
        const int rho = 9 * ((m4 >> 1) * 8 + l8) + warp;
        uint32_t base[4];
#pragma unroll
        for (int mt = 0; mt < 4; mt++) base[mt] = (sb + SM_RING + rho * 128 + (((m4 & 1) ^ (rho & 7)) << 4)) ^ (mt << 5);
        float* dst = reinterpret_cast<float*>(g_s.out) + bid * 576 + warp * 64 + 16 * j4 + 2 * g8;
        uint32_t js = j4, of_addr = sb + SM_OF + j4 * 32;
        asm volatile("" : "+r"(base[0]), "+r"(base[1]), "+r"(base[2]), "+r"(base[3]), "+l"(dst), "+r"(js), "+r"(of_addr));
        uint32_t wa[2][4][4];
#define LOAD_W(t) _Pragma("unroll") for (int mt = 0; mt < 4; mt++) ldsm4t(wa[(t) & 1][mt], base[mt] + ((t) ? ((t) - 1) * 18432 : 5 * TILE))
#define MMA_W(t, b0, b1) _Pragma("unroll") for (int mt = 0; mt < 4; mt++) mma16816(acc[(t) & 1][mt], wa[(t) & 1][mt], b0, b1)
        auto pick = [&](int a, int e) {
            float r;
            asm("{\n .reg .pred p, q;\n .reg .f32 u, v;\n .reg .b32 t;\n and.b32 t, %5, 1;\n setp.ne.u32 p, t, 0;\n setp.gt.u32 q, %5, 1;\n"
                " selp.f32 u, %2, %1, p;\n selp.f32 v, %4, %3, p;\n selp.f32 %0, v, u, q;\n}"
                : "=f"(r) : "f"(acc[a][0][e]), "f"(acc[a][1][e]), "f"(acc[a][2][e]), "f"(acc[a][3][e]), "r"(js));
            return r;
        };
        mbar_wait(bar_ofa, 0);
        const uint4 o0 = lds128(of_addr);
        const float2 o1 = lds64f(of_addr + 16);
        mbar_wait(bar_wo, 0);
        LOAD_W(0);
        MMA_W(0, o0.x, o0.y);
        mbar_wait(bar_wo + 8, 0);
        LOAD_W(1);
        MMA_W(1, o0.z, o0.w);
        mbar_wait(bar_wo + 16, 0);
        LOAD_W(2);
        const bool have_w = mbar_test(bar_wo + 24, 0);
        if (have_w) { LOAD_W(3); }
        MMA_W(2, __float_as_uint(o1.x), __float_as_uint(o1.y));
        float2 o2;
        bool have_o = false;
        if (!have_w) {
            uint32_t n = 0;
            while (!mbar_test(bar_wo + 24, 0)) {
                if (mbar_test(bar_of, 0)) {
                    o2 = lds64f(of_addr + 24);
                    have_o = true;
                    mbar_wait(bar_wo + 24, 0);
                    break;
                }
                if (++n > (SPIN_LIMIT << 4)) __trap();
            }
            LOAD_W(3);
        }
        if (!have_o) { mbar_wait(bar_of, 0); o2 = lds64f(of_addr + 24); }
        MMA_W(3, __float_as_uint(o2.x), __float_as_uint(o2.y));
        stg64(dst, nz(pick(0, 0) + pick(1, 0)), nz(pick(0, 2) + pick(1, 2)));
#undef LOAD_W
#undef MMA_W
    }
}

typedef CUresult (*EncodeFn)(CUtensorMap*, CUtensorMapDataType, cuuint32_t, void*, const cuuint64_t*, const cuuint64_t*,
                             const cuuint32_t*, const cuuint32_t*, CUtensorMapInterleave, CUtensorMapSwizzle,
                             CUtensorMapL2promotion, CUtensorMapFloatOOBfill);

}

extern "C" void kernel_launch(void* const* d_in, const int* in_sizes, int n_in, void* d_out, int out_size) {
    (void)in_sizes; (void)n_in; (void)out_size;
    static EncodeFn enc = nullptr;
    if (!enc) {
        cudaDriverEntryPointQueryResult qr;
        void* fn = nullptr;
        cudaGetDriverEntryPoint("cuTensorMapEncodeTiled", &fn, cudaEnableDefault, &qr);
        enc = (EncodeFn)fn;
        cudaFuncSetAttribute(gqa2_decode_kernel, cudaFuncAttributeMaxDynamicSharedMemorySize, SM_TOTAL);
    }
    Params prm;
    const cuuint32_t es[4] = {1, 1, 1, 1};
    for (int p = 0; p < 2; p++) {
        prm.x[p] = (const __nv_bfloat16*)d_in[5 * p + 0];
        void* ptr[4] = {d_in[5 * p + 3], d_in[5 * p + 1], d_in[5 * p + 2], d_in[5 * p + 4]};
        const cuuint64_t gd[4][4] = {{4096, 576, 1, 1}, {64, 8, 2, 16 * 8192 / 8}, {64, 8, 2, 16 * 8192 / 8}, {64, 4096 * 9, 1, 1}};
        const cuuint64_t gs[4][3] = {{8192, 8192 * 576, 8192 * 576}, {256, 128, 2048}, {256, 128, 2048}, {128, 128 * 4096 * 9, 128 * 4096 * 9}};
        const cuuint32_t bd[4][4] = {{64, 96, 1, 1}, {64, 8, 2, 8}, {64, 8, 2, 8}, {64, 144, 1, 1}};
        for (int i = 0; i < 4; i++)
            enc(&prm.tm[p][i], CU_TENSOR_MAP_DATA_TYPE_BFLOAT16, 4, ptr[i], gd[i], gs[i], bd[i], es,
                CU_TENSOR_MAP_INTERLEAVE_NONE, CU_TENSOR_MAP_SWIZZLE_128B, CU_TENSOR_MAP_L2_PROMOTION_L2_128B,
                CU_TENSOR_MAP_FLOAT_OOB_FILL_NONE);
    }
    prm.out = (__nv_bfloat16*)d_out;
    gqa2_decode_kernel<<<128, NTHREADS, SM_TOTAL>>>(prm);
}
```

```cpp
#include <cuda_runtime.h>
#include <cuda_bf16.h>
#include <cuda.h>
#include <stdint.h>

namespace {

constexpr int TILE = 32768;
constexpr int NST  = 6;
constexpr int DEPTH = 4;
constexpr int NTHREADS = 416;

constexpr int SM_RING = 0;
constexpr int SM_SC   = NST * TILE;
constexpr int SM_P    = SM_SC + 16384;
constexpr int SM_Q    = SM_P;
constexpr int SM_X    = SM_P + 8192;
constexpr int SM_RED  = SM_X + 1152;
constexpr int SM_OF   = SM_RED + 512;
constexpr int SM_PROG = SM_OF + 128;
constexpr int SM_BAR  = SM_PROG + 16;
constexpr int SM_TOTAL = SM_BAR + 320 + 1024;

struct alignas(64) Params {
    CUtensorMap tm[2][4];
    const __nv_bfloat16* x[2];
    __nv_bfloat16* out;
};

struct alignas(4096) Scratch {
    float4 out[128 * 144];
    float4 part[128 * 256];
    uint4  q[128 * 8];
    float4 stat[8 * 64];
    unsigned int cnt[3 * 32];
};
__device__ Scratch g_s;

constexpr uint32_t SPIN_LIMIT = 1u << 24;

__device__ __forceinline__ void mbar_init(uint32_t a, uint32_t c) {
    asm volatile("mbarrier.init.shared::cta.b64 [%0], %1;" ::"r"(a), "r"(c) : "memory");
}
__device__ __forceinline__ void mbar_expect(uint32_t a, uint32_t b) {
    asm volatile("mbarrier.arrive.expect_tx.shared::cta.b64 _, [%0], %1;" ::"r"(a), "r"(b) : "memory");
}
__device__ __forceinline__ void mbar_arrive(uint32_t a) {
    asm volatile("mbarrier.arrive.shared::cta.b64 _, [%0];" ::"r"(a) : "memory");
}
__device__ __forceinline__ void mbar_wait(uint32_t a, uint32_t ph) {
    uint32_t ok, n = 0;
    do {
        asm volatile("{\n .reg .pred p;\n mbarrier.try_wait.parity.shared::cta.b64 p, [%1], %2;\n selp.u32 %0, 1, 0, p;\n}"
                     : "=r"(ok) : "r"(a), "r"(ph) : "memory");
        if (++n > SPIN_LIMIT) __trap();
    } while (!ok);
}
__device__ __forceinline__ bool mbar_test(uint32_t a, uint32_t ph) {
    uint32_t ok;
    asm volatile("{\n .reg .pred p;\n mbarrier.test_wait.parity.shared::cta.b64 p, [%1], %2;\n selp.u32 %0, 1, 0, p;\n}"
                 : "=r"(ok) : "r"(a), "r"(ph) : "memory");
    return __all_sync(0xffffffffu, ok != 0);
}
__device__ __forceinline__ void tma4d(uint32_t dst, const CUtensorMap* tm, int c0, int c1, int c3, uint32_t mbar, uint64_t pol) {
    asm volatile("cp.async.bulk.tensor.4d.shared::cluster.global.mbarrier::complete_tx::bytes.L2::cache_hint"
                 " [%0], [%1, {%3, %4, %5, %6}], [%2], %7;"
                 ::"r"(dst), "l"(tm), "r"(mbar), "r"(c0), "r"(c1), "r"(0), "r"(c3), "l"(pol) : "memory");
}
__device__ __forceinline__ void ldsm4(uint32_t (&r)[4], uint32_t a) {
    asm volatile("ldmatrix.sync.aligned.m8n8.x4.shared.b16 {%0,%1,%2,%3}, [%4];"
                 : "=r"(r[0]), "=r"(r[1]), "=r"(r[2]), "=r"(r[3]) : "r"(a) : "memory");
}
__device__ __forceinline__ void ldsm4t(uint32_t (&r)[4], uint32_t a) {
    asm volatile("ldmatrix.sync.aligned.m8n8.x4.trans.shared.b16 {%0,%1,%2,%3}, [%4];"
                 : "=r"(r[0]), "=r"(r[1]), "=r"(r[2]), "=r"(r[3]) : "r"(a) : "memory");
}
__device__ __forceinline__ void mma16816(float (&c)[4], const uint32_t (&a)[4], uint32_t b0, uint32_t b1) {
    asm volatile("mma.sync.aligned.m16n8k16.row.col.f32.bf16.bf16.f32 {%0,%1,%2,%3}, {%4,%5,%6,%7}, {%8,%9}, {%0,%1,%2,%3};"
                 : "+f"(c[0]), "+f"(c[1]), "+f"(c[2]), "+f"(c[3])
                 : "r"(a[0]), "r"(a[1]), "r"(a[2]), "r"(a[3]), "r"(b0), "r"(b1));
}
__device__ __forceinline__ uint4 lds128(uint32_t a) {
    uint4 v;
    asm volatile("ld.shared.v4.u32 {%0,%1,%2,%3}, [%4];" : "=r"(v.x), "=r"(v.y), "=r"(v.z), "=r"(v.w) : "r"(a) : "memory");
    return v;
}
__device__ __forceinline__ float4 lds128f(uint32_t a) {
    float4 v;
    asm volatile("ld.shared.v4.f32 {%0,%1,%2,%3}, [%4];" : "=f"(v.x), "=f"(v.y), "=f"(v.z), "=f"(v.w) : "r"(a) : "memory");
    return v;
}
__device__ __forceinline__ float2 lds64f(uint32_t a) {
    float2 v;
    asm volatile("ld.shared.v2.f32 {%0,%1}, [%2];" : "=f"(v.x), "=f"(v.y) : "r"(a) : "memory");
    return v;
}
__device__ __forceinline__ uint32_t lds32v(uint32_t a) {
    uint32_t v;
    asm volatile("ld.volatile.shared.u32 %0, [%1];" : "=r"(v) : "r"(a) : "memory");
    return v;
}
__device__ __forceinline__ void sts128(uint32_t a, uint4 v) {
    asm volatile("st.shared.v4.u32 [%0], {%1,%2,%3,%4};" ::"r"(a), "r"(v.x), "r"(v.y), "r"(v.z), "r"(v.w) : "memory");
}
__device__ __forceinline__ void sts64(uint32_t a, uint32_t x, uint32_t y) {
    asm volatile("st.shared.v2.u32 [%0], {%1,%2};" ::"r"(a), "r"(x), "r"(y) : "memory");
}
__device__ __forceinline__ void sts32(uint32_t a, uint32_t x) {
    asm volatile("st.volatile.shared.u32 [%0], %1;" ::"r"(a), "r"(x) : "memory");
}
__device__ __forceinline__ void poll128(uint4& v, const void* p, bool pred) {
    asm volatile("{\n .reg .pred p;\n setp.ne.u32 p, %5, 0;\n @p ld.relaxed.gpu.global.v4.u32 {%0,%1,%2,%3}, [%4];\n}"
                 : "+r"(v.x), "+r"(v.y), "+r"(v.z), "+r"(v.w) : "l"(p), "r"((uint32_t)pred) : "memory");
}
__device__ __forceinline__ void stg128(void* p, uint4 v) {
    asm volatile("st.relaxed.gpu.global.v4.u32 [%0], {%1,%2,%3,%4};" ::"l"(p), "r"(v.x), "r"(v.y), "r"(v.z), "r"(v.w) : "memory");
}
__device__ __forceinline__ void stg64(void* p, uint32_t x, uint32_t y) {
    asm volatile("st.relaxed.gpu.global.v2.u32 [%0], {%1,%2};" ::"l"(p), "r"(x), "r"(y) : "memory");
}
__device__ __forceinline__ void stg32(void* p, uint32_t x) {
    asm volatile("st.relaxed.gpu.global.u32 [%0], %1;" ::"l"(p), "r"(x) : "memory");
}
__device__ __forceinline__ uint32_t nz(float f) {
    uint32_t u = __float_as_uint(f);
    return u == 0u ? 0x80000000u : u;
}
__device__ __forceinline__ bool all_set(const uint4& v) { return v.x != 0u && v.y != 0u && v.z != 0u && v.w != 0u; }
__device__ __forceinline__ void poll2(uint4& a, const void* pa, uint4& b, const void* pb, int sleep_ns) {
    uint32_t n = 0;
    while (true) {
        const bool ma = !all_set(a), mb = !all_set(b);
        if (!__any_sync(0xffffffffu, ma || mb)) break;
        if (sleep_ns && n) __nanosleep(sleep_ns);
        poll128(a, pa, ma);
        poll128(b, pb, mb);
        if (++n > SPIN_LIMIT) __trap();
    }
}
__device__ __forceinline__ uint32_t pack_bf16(float lo, float hi) {
    uint32_t r;
    asm("cvt.rn.bf16x2.f32 %0, %1, %2;" : "=r"(r) : "f"(hi), "f"(lo));
    return r;
}
__device__ __forceinline__ float ex2(float x) {
    float r;
    asm("ex2.approx.ftz.f32 %0, %1;" : "=f"(r) : "f"(x));
    return r;
}
__device__ __forceinline__ float sel4(const float (&c)[4], int j) {
    float a = (j & 1) ? c[1] : c[0];
    float b = (j & 1) ? c[3] : c[2];
    return (j & 2) ? b : a;
}
__device__ __forceinline__ bool elect_one() {
    uint32_t p;
    asm volatile("{\n .reg .pred p;\n elect.sync _|p, 0xffffffff;\n selp.u32 %0, 1, 0, p;\n}" : "=r"(p));
    return p != 0;
}
__device__ __forceinline__ void bar_consumers() { asm volatile("bar.sync 1, 256;" ::: "memory"); }

__global__ void __launch_bounds__(NTHREADS, 1)
gqa2_decode_kernel(const __grid_constant__ Params prm) {
    extern __shared__ unsigned char smem_raw[];
    const uint32_t sb = ((uint32_t)__cvta_generic_to_shared(smem_raw) + 1023u) & ~1023u;
    const int tid = threadIdx.x, warp = tid >> 5, lane = tid & 31;
    const int bid = blockIdx.x, prob = bid >> 6, c = bid & 63;
    const uint32_t bar_full = sb + SM_BAR, bar_wo = bar_full + 16 * NST, bar_empty = bar_wo + 32;
    const uint32_t bar_ready = bar_empty + 8 * NST, bar_x = bar_ready + 8, bar_of = bar_ready + 16,
                   bar_go = bar_ready + 24, bar_ofa = bar_ready + 56, bar_gd = bar_ready + 64;

    int wu = __shfl_sync(0xffffffffu, warp, 0);
    if (wu == 8) {
        uint64_t pol;
        asm volatile("createpolicy.fractional.L2::evict_first.b64 %0, 1.0;" : "=l"(pol));
        if (elect_one()) {
#pragma unroll
            for (int s = 0; s < 2 * NST; s++) mbar_init(bar_full + 8 * s, 1);
            asm volatile("fence.mbarrier_init.release.cluster;" ::: "memory");
#pragma unroll
            for (int n = 0; n < DEPTH; n++) {
                mbar_expect(bar_full + 8 * n, 12288);
                tma4d(sb + SM_RING + (n >> 1) * TILE + (n & 1) * 12288, &prm.tm[prob][0], c * 64, n * 96, 0, bar_full + 8 * n, pol);
            }
#pragma unroll
            for (int s = 0; s < 4; s++) mbar_init(bar_wo + 8 * s, 1);
#pragma unroll
            for (int s = 0; s < NST; s++) mbar_init(bar_empty + 8 * s, 8);
#pragma unroll
            for (int s = 0; s < 7; s++) mbar_init(bar_ready + 8 * s, 1);
            mbar_init(bar_ofa, 3);
            mbar_init(bar_gd, 9);
            asm volatile("fence.mbarrier_init.release.cluster;" ::: "memory");
            mbar_expect(bar_x, 1152);
            asm volatile("cp.async.bulk.shared::cluster.global.mbarrier::complete_tx::bytes [%0], [%1], 1152, [%2];"
                         ::"r"(sb + SM_X), "l"(prm.x[prob]), "r"(bar_x) : "memory");
            sts64(sb + SM_PROG, 0u, 0u);
#pragma unroll
            for (int k = 1; k < 4; k++) asm volatile("prefetch.tensormap [%0];" ::"l"(&prm.tm[prob][k]) : "memory");
        }
        __syncwarp();
        asm volatile("bar.arrive 3, %0;" ::"n"(NTHREADS) : "memory");
        int ib = DEPTH, iph = 0;
        int nw = 0, wb = 0, wph = 0;
#pragma unroll 1
        for (int n = DEPTH; n < 70; n++) {
            const bool kv = n >= 6;
            const int bytes = kv ? TILE / 2 : 12288;
            const uint32_t dst = sb + SM_RING + (ib >> 1) * TILE + (ib & 1) * bytes, bar = bar_full + 8 * ib;
            if (n >= 2 * NST && (n & 1) == 0) mbar_wait(bar_empty + 4 * ib, iph ^ 1);
            if (elect_one()) mbar_expect(bar, bytes);
            while (true) {
                int win = DEPTH;
                if (n >= 10) {
                    const int lag = (int)(lds32v(sb + SM_PROG) & 8191u) - ((n - 6) * 128 - 320);
                    win = min(max(DEPTH + (lag >> 7), 2), 8);
                }
                if (n - nw < win) break;
                mbar_wait(bar_full + 8 * wb, wph);
                nw++;
                if (++wb == 2 * NST) { wb = 0; wph ^= 1; }
            }
            if (elect_one()) {
                tma4d(dst, &prm.tm[prob][kv + (n >= 38)], kv ? 0 : c * 64, kv ? 0 : n * 96, kv ? (((n - 6) & 31) >> 3) * 4096 + (c >> 4) * 1024 + ((n - 6) & 7) * 128 + (c & 15) * 8 : 0, bar, pol);
                if (kv) sts32(sb + SM_PROG + 4, n - 5);
            }
            if (++ib == 2 * NST) { ib = 0; iph ^= 1; }
        }
#pragma unroll
        for (int k = 0; k < 4; k++) {
            if (k == 0) mbar_wait(bar_empty + 40, 0);
            else if (k < 3) mbar_wait(bar_empty + 8 * (k - 1), 1);
            mbar_wait(bar_full + 8 * ((70 + k - DEPTH) % 12), ((70 + k - DEPTH) / 12) & 1);
            if (elect_one())
                tma4d(sb + SM_RING + (k ? (k - 1) * 18432 : 5 * TILE), &prm.tm[prob][3], 0, (k * 1024 + c * 16) * 9, 0, bar_wo + 8 * k, pol);
        }
    } else {
        asm volatile("bar.sync 3, %0;" ::"n"(NTHREADS) : "memory");
    }
    asm volatile("" : "+r"(wu));
    const int g8 = lane >> 2, j4 = lane & 3, l8 = lane & 7, m4 = lane >> 3;
    const uint4 zero4 = make_uint4(0u, 0u, 0u, 0u);

    if (wu == 9) {
        float4* const psrc = g_s.part + bid * 256 + lane;
#pragma unroll
        for (int i = 0; i < 8; i++) stg128(psrc + 32 * i, zero4);
#pragma unroll
        for (int i = 0; i < 4; i++) stg128(g_s.out + bid * 144 + i * 32 + lane, zero4);
        if (lane < 16) stg128(g_s.out + bid * 144 + 128 + lane, zero4);
        else if (lane < 20) stg128(g_s.stat + bid * 4 + (lane - 16), zero4);
        __syncwarp();
        if (lane == 0) {
            unsigned int v, n = 0;
            asm volatile("atom.release.gpu.global.add.u32 %0, [%1], 1;" : "=r"(v) : "l"(g_s.cnt + prob * 32) : "memory");
            const unsigned int target = (v & ~63u) + 64u;
            do {
                __nanosleep(5000);
                asm volatile("ld.relaxed.gpu.global.u32 %0, [%1];" : "=r"(v) : "l"(g_s.cnt + prob * 32) : "memory");
                if (++n > SPIN_LIMIT) __trap();
            } while ((int)(v - target) < 0);
            asm volatile("ld.acquire.gpu.global.u32 %0, [%1];" : "=r"(v) : "l"(g_s.cnt + prob * 32) : "memory");
            mbar_arrive(bar_ready);
        }
        __syncwarp();
        mbar_wait(bar_go, 0);
        float e0, e1;
        {
            uint4 sa = zero4, dummy = make_uint4(1u, 1u, 1u, 1u);
            poll2(sa, g_s.stat + (bid >> 3) * 32 + lane, dummy, g_s.stat, 300);
            if (lane < 8) stg128(g_s.q + (prob * 16 + ((c >> 2) & 3) * 4 + (c >> 4)) * 32 + (c & 3) * 8 + lane, zero4);
            const float m0 = __uint_as_float(sa.x), m1 = __uint_as_float(sa.z);
            float M = fmaxf(m0, m1);
#pragma unroll
            for (int o = 4; o > 0; o >>= 1) M = fmaxf(M, __shfl_xor_sync(0xffffffffu, M, o));
            e0 = ex2(m0 - M); e1 = ex2(m1 - M);
            float L = e0 * __uint_as_float(sa.y) + e1 * __uint_as_float(sa.w);
#pragma unroll
            for (int o = 4; o > 0; o >>= 1) L += __shfl_xor_sync(0xffffffffu, L, o);
            const float inv = 1.0f / L;
            e0 *= inv; e1 *= inv;
        }
        const bool up = lane >= 16;
        const int pr = 2 * j4 + (up ? 1 : 0);
        const uint32_t of_addr = sb + SM_OF + ((pr & 3) * 8 + (pr >> 2)) * 4;
#pragma unroll 1
        for (int t = 0; t < 4; t++) {
            const float a0 = __shfl_sync(0xffffffffu, e0, 8 * t + (g8 >> 1)), a1 = __shfl_sync(0xffffffffu, e1, 8 * t + (g8 >> 1));
            const float b0 = __shfl_sync(0xffffffffu, e0, 8 * t + 4 + (g8 >> 1)), b1 = __shfl_sync(0xffffffffu, e1, 8 * t + 4 + (g8 >> 1));
            const float w0 = (g8 & 1) ? a1 : a0, w1 = (g8 & 1) ? b1 : b0;
            mbar_wait(bar_go + 8 * t, 0);
            uint4 pa = zero4, pb = zero4;
            poll2(pa, psrc + 64 * t, pb, psrc + 64 * t + 32, t < 3 ? 300 : 0);
            const float x = w0 * __uint_as_float(pa.x) + w1 * __uint_as_float(pb.x), y = w0 * __uint_as_float(pa.y) + w1 * __uint_as_float(pb.y);
            const float z = w0 * __uint_as_float(pa.z) + w1 * __uint_as_float(pb.z), w = w0 * __uint_as_float(pa.w) + w1 * __uint_as_float(pb.w);
            float k0 = (up ? z : x) + __shfl_xor_sync(0xffffffffu, up ? x : z, 16);
            float k1 = (up ? w : y) + __shfl_xor_sync(0xffffffffu, up ? y : w, 16);
#pragma unroll
            for (int o = 8; o > 2; o >>= 1) {
                k0 += __shfl_xor_sync(0xffffffffu, k0, o);
                k1 += __shfl_xor_sync(0xffffffffu, k1, o);
            }
            if ((lane & 12) == 0) sts32(of_addr + 8 * t, pack_bf16(k0, k1));
            __syncwarp();
            if (lane == 0) mbar_arrive(t < 3 ? bar_ofa : bar_of);
        }
        return;
    } else if (wu > 9) {
        if (wu == 10 && lane < 4) mbar_expect(bar_wo + 8 * lane, 18432);
        if (wu == 12) {
            if (lane == 0) {
                uint32_t rep = 0, n = 0;
                while (rep < 64u) {
                    const uint32_t cur = lds32v(sb + SM_PROG + 4);
                    if (cur == rep) { __nanosleep(40); if (++n > SPIN_LIMIT) __trap(); continue; }
                    uint32_t v;
                    asm volatile("atom.relaxed.gpu.global.add.u32 %0, [%1], %2;" : "=r"(v) : "l"(g_s.cnt + 64), "r"(cur - rep) : "memory");
                    sts32(sb + SM_PROG, v);
                    rep = cur;
                }
            }
            __syncwarp();
        }
        const int u = (wu - 10) * 64 + c;
        if (u >= 144) return;
        const float4* const osrc = g_s.out + (prob * 64 + lane) * 144 + u;
        const bool up = lane >= 16;
        uint32_t* const optr = reinterpret_cast<uint32_t*>(prm.out + prob * 576 + 16 * (u >> 2) + 2 * (u & 3) + (up ? 8 : 0));
        mbar_wait(bar_gd, 0);
        uint4 a = zero4, b = zero4;
        poll2(a, osrc, b, osrc + 32 * 144, 0);
        const float x = __uint_as_float(a.x) + __uint_as_float(b.x), y = __uint_as_float(a.y) + __uint_as_float(b.y);
        const float z = __uint_as_float(a.z) + __uint_as_float(b.z), w = __uint_as_float(a.w) + __uint_as_float(b.w);
        float k0 = (up ? y : x) + __shfl_xor_sync(0xffffffffu, up ? x : y, 16);
        float k1 = (up ? w : z) + __shfl_xor_sync(0xffffffffu, up ? z : w, 16);
#pragma unroll
        for (int o = 8; o > 0; o >>= 1) {
            k0 += __shfl_xor_sync(0xffffffffu, k0, o);
            k1 += __shfl_xor_sync(0xffffffffu, k1, o);
        }
        if ((lane & 15) == 0) *optr = pack_bf16(k0, k1);
        return;
    } else if (wu < 8) {
        {
            uint32_t xb[3][12];
            mbar_wait(bar_x, 0);
#pragma unroll
            for (int b = 0; b < 3; b++)
#pragma unroll
                for (int t = 0; t < 12; t++) xb[b][t] = lds32v(sb + SM_X + ((warp >> 2) * 48 + j4 + b * 96 + 4 * t) * 4);
            float c0[4] = {0.f, 0.f, 0.f, 0.f}, c1[4] = {0.f, 0.f, 0.f, 0.f};
            const uint32_t base = sb + SM_RING + ((warp >> 2) * 96 + (m4 >> 1) * 8 + l8) * 128 + (((2 * (warp & 3) + (m4 & 1)) ^ l8) << 4);
#pragma unroll
            for (int b = 0; b < 3; b++) {
                mbar_wait(bar_full + 16 * b + 8 * (warp >> 2), 0);
#pragma unroll
                for (int t = 0; t < 3; t++) {
                    uint32_t a0[4], a1[4];
                    ldsm4t(a0, base + b * TILE + (2 * t) * 2048);
                    ldsm4t(a1, base + b * TILE + (2 * t + 1) * 2048);
                    mma16816(c0, a0, xb[b][4 * t], xb[b][4 * t + 1]);
                    mma16816(c1, a1, xb[b][4 * t + 2], xb[b][4 * t + 3]);
                }
                __syncwarp();
                if (lane == 0) mbar_arrive(bar_empty + 8 * b);
            }
            if (j4 < 2) sts32(sb + SM_RED + (warp * 16 + g8 + 8 * j4) * 4, __float_as_uint(j4 ? c0[2] + c1[2] : c0[0] + c1[0]));
        }
        bar_consumers();
        if (warp == 0) {
            const float2 va = lds64f(sb + SM_RED + lane * 8), vb = lds64f(sb + SM_RED + 256 + lane * 8);
            uint32_t u = pack_bf16(va.x + vb.x, va.y + vb.y);
            if (u == 0u) u = 0x8000u;
            const int d = 64 * (c & 1) + 2 * lane;
            const int w16 = 2 * (d >> 4) + ((d >> 3) & 1);
            stg32(reinterpret_cast<uint32_t*>(g_s.q) + (bid >> 2) * 128 + (w16 >> 2) * 32 + ((c >> 1) & 1) * 16 + ((d & 7) >> 1) * 4 + (w16 & 3), u);
        }
        if (warp < 4) {
            uint4 v = zero4, dummy = make_uint4(1u, 1u, 1u, 1u);
            mbar_wait(bar_full + 8 * 8, 0);
            poll2(v, g_s.q + (prob * 16 + warp * 4 + (c >> 4)) * 32 + lane, dummy, g_s.q, 300);
            sts128(sb + SM_Q + warp * 512 + lane * 16, v);
        }
        bar_consumers();
        const uint32_t frag_off = (g8 & 1) * 64 + j4 * 16;
        int s = 3, ph = 0;

        {
            const uint32_t kbase = sb + SM_RING + (2 * warp + (m4 & 1)) * 2048 + l8 * 128 + (((m4 >> 1) ^ l8) << 4);
            const uint32_t sc_addr = sb + SM_SC + (warp * 32 + (j4 & 1) * 16 + (g8 >> 1) * 4 + (g8 & 1) + (j4 >> 1) * 2) * 4;
            uint4 qb[4];
#pragma unroll 1
            for (int i = 0; i < 16; i++) {
                if ((i & 3) == 0) {
#pragma unroll
                    for (int q = 0; q < 4; q++) qb[q] = lds128(sb + SM_Q + (i >> 2) * 512 + q * 128 + frag_off);
                }
                mbar_wait(bar_full + 16 * s + 8 * (warp >> 2), ph);
                float c0[4] = {0.f, 0.f, 0.f, 0.f}, c1[4] = {0.f, 0.f, 0.f, 0.f};
                const uint32_t kb = kbase + s * TILE;
#pragma unroll
                for (int q = 0; q < 4; q++) {
                    uint32_t a0[4], a1[4];
                    ldsm4(a0, (kb ^ (((2 * q) & 3) << 5)) + (q >> 1) * 1024);
                    ldsm4(a1, (kb ^ (((2 * q + 1) & 3) << 5)) + (q >> 1) * 1024);
                    mma16816(c0, a0, qb[q].x, qb[q].y);
                    mma16816(c1, a1, qb[q].z, qb[q].w);
                }
                __syncwarp();
                if (lane == 0) mbar_arrive(bar_empty + 8 * s);
                sts32(sc_addr + i * 1024, __float_as_uint(sel4(c0, j4) + sel4(c1, j4)));
                if (++s == NST) { s = 0; ph ^= 1; }
            }
        }
        mbar_wait(bar_ready, 0);
        bar_consumers();

        {
            constexpr float SCALE = 0.08838834764831845f * 1.4426950408889634f;
            const int hd = warp & 1, st = warp >> 1;
            float4 sv[4];
            float ms = -INFINITY, sum = 0.f;
#pragma unroll
            for (int t = 0; t < 4; t++) {
                sv[t] = lds128f(sb + SM_SC + ((4 * st + t) * 256 + g8 * 32 + hd * 16 + j4 * 4) * 4);
                ms = fmaxf(ms, fmaxf(fmaxf(sv[t].x, sv[t].y), fmaxf(sv[t].z, sv[t].w)));
            }
#pragma unroll
            for (int o = 16; o > 0; o >>= 1) ms = fmaxf(ms, __shfl_xor_sync(0xffffffffu, ms, o));
            ms *= SCALE;
#pragma unroll
            for (int t = 0; t < 4; t++) {
                const float p0 = ex2(fmaf(sv[t].x, SCALE, -ms)), p1 = ex2(fmaf(sv[t].y, SCALE, -ms));
                const float p2 = ex2(fmaf(sv[t].z, SCALE, -ms)), p3 = ex2(fmaf(sv[t].w, SCALE, -ms));
                sum += (p0 + p1) + (p2 + p3);
                sts64(sb + SM_P + (4 * st + t) * 512 + (g8 >> 1) * 128 + hd * 64 + j4 * 16 + (g8 & 1) * 8, pack_bf16(p0, p1), pack_bf16(p2, p3));
            }
            bar_consumers();
#pragma unroll
            for (int o = 16; o > 0; o >>= 1) sum += __shfl_xor_sync(0xffffffffu, sum, o);
            if (lane == 0) stg64(reinterpret_cast<float2*>(g_s.stat) + (((bid >> 4) * 2 + hd) * 4 + st) * 16 + (c & 15), nz(ms), nz(sum));
        }

        {
            const uint32_t vbase = sb + SM_RING + (m4 >> 1) * 2048 + (warp >> 2) * 1024 + l8 * 128 + (((2 * (warp & 3) + (m4 & 1)) ^ l8) << 4);
            float* dst = reinterpret_cast<float*>(g_s.part) + ((bid & ~15) + 8 * (j4 & 1) + warp) * 1024 + (c & 15) * 16 + g8 + 8 * (j4 >> 1);
            float c0[4] = {0.f, 0.f, 0.f, 0.f}, c1[4] = {0.f, 0.f, 0.f, 0.f};
#pragma unroll 1
            for (int i = 0; i < 16; i++) {
                uint4 pb[4];
#pragma unroll
                for (int q = 0; q < 4; q++) pb[q] = lds128(sb + SM_P + i * 512 + q * 128 + frag_off);
                const uint32_t vb = vbase + s * TILE;
#pragma unroll
                for (int q = 0; q < 4; q++) {
                    uint32_t a0[4], a1[4];
                    if ((q & 1) == 0) mbar_wait(bar_full + 16 * s + 4 * q, ph);
                    ldsm4t(a0, vb + (2 * q) * 4096);
                    ldsm4t(a1, vb + (2 * q + 1) * 4096);
                    mma16816(c0, a0, pb[q].x, pb[q].y);
                    mma16816(c1, a1, pb[q].z, pb[q].w);
                }
                __syncwarp();
                if (lane == 0) mbar_arrive(bar_empty + 8 * s);
                if ((i & 3) == 3) {
                    stg32(dst, nz(sel4(c0, j4) + sel4(c1, j4)));
                    dst += 256;
#pragma unroll
                    for (int e = 0; e < 4; e++) { c0[e] = 0.f; c1[e] = 0.f; }
                }
                if (tid == 0 && (i == 15 || (i > 4 && (i & 3) == 1))) mbar_arrive(bar_go + (i == 15 ? 24 : 2 * (i - 5)));
                if (++s == NST) { s = 0; ph ^= 1; }
            }
        }
    }

    {
        float acc[2][4][4];
#pragma unroll
        for (int e = 0; e < 32; e++) (&acc[0][0][0])[e] = 0.f;
        const int rho = 9 * ((m4 >> 1) * 8 + l8) + warp;
        uint32_t base[4];
#pragma unroll
        for (int mt = 0; mt < 4; mt++) base[mt] = (sb + SM_RING + rho * 128 + (((m4 & 1) ^ (rho & 7)) << 4)) ^ (mt << 5);
        float* dst = reinterpret_cast<float*>(g_s.out) + bid * 576 + warp * 64 + 16 * j4 + 2 * g8;
        uint32_t js = j4, of_addr = sb + SM_OF + j4 * 32;
        asm volatile("" : "+r"(base[0]), "+r"(base[1]), "+r"(base[2]), "+r"(base[3]), "+l"(dst), "+r"(js), "+r"(of_addr));
        uint32_t wa[2][4][4];
#define LOAD_W(t) _Pragma("unroll") for (int mt = 0; mt < 4; mt++) ldsm4t(wa[(t) & 1][mt], base[mt] + ((t) ? ((t) - 1) * 18432 : 5 * TILE))
#define MMA_W(t, b0, b1) _Pragma("unroll") for (int mt = 0; mt < 4; mt++) mma16816(acc[(t) & 1][mt], wa[(t) & 1][mt], b0, b1)
        auto pick = [&](int a, int e) {
            float r;
            asm("{\n .reg .pred p, q;\n .reg .f32 u, v;\n .reg .b32 t;\n and.b32 t, %5, 1;\n setp.ne.u32 p, t, 0;\n setp.gt.u32 q, %5, 1;\n"
                " selp.f32 u, %2, %1, p;\n selp.f32 v, %4, %3, p;\n selp.f32 %0, v, u, q;\n}"
                : "=f"(r) : "f"(acc[a][0][e]), "f"(acc[a][1][e]), "f"(acc[a][2][e]), "f"(acc[a][3][e]), "r"(js));
            return r;
        };
        mbar_wait(bar_ofa, 0);
        const uint4 o0 = lds128(of_addr);
        const float2 o1 = lds64f(of_addr + 16);
        mbar_wait(bar_wo, 0);
        LOAD_W(0);
        MMA_W(0, o0.x, o0.y);
        mbar_wait(bar_wo + 8, 0);
        LOAD_W(1);
        MMA_W(1, o0.z, o0.w);
        mbar_wait(bar_wo + 16, 0);
        LOAD_W(2);
        const bool have_w = mbar_test(bar_wo + 24, 0);
        if (have_w) { LOAD_W(3); }
        MMA_W(2, __float_as_uint(o1.x), __float_as_uint(o1.y));
        float2 o2;
        bool have_o = false;
        if (!have_w) {
            uint32_t n = 0;
            while (!mbar_test(bar_wo + 24, 0)) {
                if (mbar_test(bar_of, 0)) {
                    o2 = lds64f(of_addr + 24);
                    have_o = true;
                    mbar_wait(bar_wo + 24, 0);
                    break;
                }
                if (++n > (SPIN_LIMIT << 4)) __trap();
            }
            LOAD_W(3);
        }
        if (!have_o) { mbar_wait(bar_of, 0); o2 = lds64f(of_addr + 24); }
        MMA_W(3, __float_as_uint(o2.x), __float_as_uint(o2.y));
        stg64(dst, nz(pick(0, 0) + pick(1, 0)), nz(pick(0, 2) + pick(1, 2)));
        if (lane == 0) mbar_arrive(bar_gd);
#undef LOAD_W
#undef MMA_W
    }
}

typedef CUresult (*EncodeFn)(CUtensorMap*, CUtensorMapDataType, cuuint32_t, void*, const cuuint64_t*, const cuuint64_t*,
                             const cuuint32_t*, const cuuint32_t*, CUtensorMapInterleave, CUtensorMapSwizzle,
                             CUtensorMapL2promotion, CUtensorMapFloatOOBfill);

}

extern "C" void kernel_launch(void* const* d_in, const int* in_sizes, int n_in, void* d_out, int out_size) {
    (void)in_sizes; (void)n_in; (void)out_size;
    static EncodeFn enc = nullptr;
    if (!enc) {
        cudaDriverEntryPointQueryResult qr;
        void* fn = nullptr;
        cudaGetDriverEntryPoint("cuTensorMapEncodeTiled", &fn, cudaEnableDefault, &qr);
        enc = (EncodeFn)fn;
        cudaFuncSetAttribute(gqa2_decode_kernel, cudaFuncAttributeMaxDynamicSharedMemorySize, SM_TOTAL);
    }
    Params prm;
    const cuuint32_t es[4] = {1, 1, 1, 1};
    for (int p = 0; p < 2; p++) {
        prm.x[p] = (const __nv_bfloat16*)d_in[5 * p + 0];
        void* ptr[4] = {d_in[5 * p + 3], d_in[5 * p + 1], d_in[5 * p + 2], d_in[5 * p + 4]};
        const cuuint64_t gd[4][4] = {{4096, 576, 1, 1}, {64, 8, 2, 16 * 8192 / 8}, {64, 8, 2, 16 * 8192 / 8}, {64, 4096 * 9, 1, 1}};
        const cuuint64_t gs[4][3] = {{8192, 8192 * 576, 8192 * 576}, {256, 128, 2048}, {256, 128, 2048}, {128, 128 * 4096 * 9, 128 * 4096 * 9}};
        const cuuint32_t bd[4][4] = {{64, 96, 1, 1}, {64, 8, 2, 8}, {64, 8, 2, 8}, {64, 144, 1, 1}};
        for (int i = 0; i < 4; i++)
            enc(&prm.tm[p][i], CU_TENSOR_MAP_DATA_TYPE_BFLOAT16, 4, ptr[i], gd[i], gs[i], bd[i], es,
                CU_TENSOR_MAP_INTERLEAVE_NONE, CU_TENSOR_MAP_SWIZZLE_128B, CU_TENSOR_MAP_L2_PROMOTION_L2_128B,
                CU_TENSOR_MAP_FLOAT_OOB_FILL_NONE);
    }
    prm.out = (__nv_bfloat16*)d_out;
    gqa2_decode_kernel<<<128, NTHREADS, SM_TOTAL>>>(prm);
}
```

```cpp
#include <cuda_runtime.h>
#include <cuda_bf16.h>
#include <cuda.h>
#include <stdint.h>

namespace {

constexpr int TILE = 32768;
constexpr int NST  = 6;
constexpr int DEPTH = 4;
constexpr int NTHREADS = 416;

constexpr int SM_RING = 0;
constexpr int SM_SC   = NST * TILE;
constexpr int SM_P    = SM_SC + 16384;
constexpr int SM_Q    = SM_P;
constexpr int SM_X    = SM_P + 8192;
constexpr int SM_RED  = SM_X + 1152;
constexpr int SM_OF   = SM_RED + 512;
constexpr int SM_PROG = SM_OF + 256;
constexpr int SM_BAR  = SM_PROG + 16;
constexpr int SM_TOTAL = SM_BAR + 320 + 1024;

struct alignas(64) Params {
    CUtensorMap tm[2][4];
    const __nv_bfloat16* x[2];
    __nv_bfloat16* out;
};

struct alignas(4096) Scratch {
    float4 out[128 * 144];
    float4 part[128 * 512];
    uint4  q[128 * 8];
    float4 stat[128 * 8];
    unsigned int cnt[3 * 32];
};
__device__ Scratch g_s;

constexpr uint32_t SPIN_LIMIT = 1u << 24;

__device__ __forceinline__ void mbar_init(uint32_t a, uint32_t c) {
    asm volatile("mbarrier.init.shared::cta.b64 [%0], %1;" ::"r"(a), "r"(c) : "memory");
}
__device__ __forceinline__ void mbar_expect(uint32_t a, uint32_t b) {
    asm volatile("mbarrier.arrive.expect_tx.shared::cta.b64 _, [%0], %1;" ::"r"(a), "r"(b) : "memory");
}
__device__ __forceinline__ void mbar_arrive(uint32_t a) {
    asm volatile("mbarrier.arrive.shared::cta.b64 _, [%0];" ::"r"(a) : "memory");
}
__device__ __forceinline__ void mbar_wait(uint32_t a, uint32_t ph) {
    uint32_t ok, n = 0;
    do {
        asm volatile("{\n .reg .pred p;\n mbarrier.try_wait.parity.shared::cta.b64 p, [%1], %2;\n selp.u32 %0, 1, 0, p;\n}"
                     : "=r"(ok) : "r"(a), "r"(ph) : "memory");
        if (++n > SPIN_LIMIT) __trap();
    } while (!ok);
}
__device__ __forceinline__ bool mbar_test(uint32_t a, uint32_t ph) {
    uint32_t ok;
    asm volatile("{\n .reg .pred p;\n mbarrier.test_wait.parity.shared::cta.b64 p, [%1], %2;\n selp.u32 %0, 1, 0, p;\n}"
                 : "=r"(ok) : "r"(a), "r"(ph) : "memory");
    return __all_sync(0xffffffffu, ok != 0);
}
__device__ __forceinline__ void tma4d(uint32_t dst, const CUtensorMap* tm, int c0, int c1, int c3, uint32_t mbar, uint64_t pol) {
    asm volatile("cp.async.bulk.tensor.4d.shared::cluster.global.mbarrier::complete_tx::bytes.L2::cache_hint"
                 " [%0], [%1, {%3, %4, %5, %6}], [%2], %7;"
                 ::"r"(dst), "l"(tm), "r"(mbar), "r"(c0), "r"(c1), "r"(0), "r"(c3), "l"(pol) : "memory");
}
__device__ __forceinline__ void ldsm4(uint32_t (&r)[4], uint32_t a) {
    asm volatile("ldmatrix.sync.aligned.m8n8.x4.shared.b16 {%0,%1,%2,%3}, [%4];"
                 : "=r"(r[0]), "=r"(r[1]), "=r"(r[2]), "=r"(r[3]) : "r"(a) : "memory");
}
__device__ __forceinline__ void ldsm4t(uint32_t (&r)[4], uint32_t a) {
    asm volatile("ldmatrix.sync.aligned.m8n8.x4.trans.shared.b16 {%0,%1,%2,%3}, [%4];"
                 : "=r"(r[0]), "=r"(r[1]), "=r"(r[2]), "=r"(r[3]) : "r"(a) : "memory");
}
__device__ __forceinline__ void mma16816(float (&c)[4], const uint32_t (&a)[4], uint32_t b0, uint32_t b1) {
    asm volatile("mma.sync.aligned.m16n8k16.row.col.f32.bf16.bf16.f32 {%0,%1,%2,%3}, {%4,%5,%6,%7}, {%8,%9}, {%0,%1,%2,%3};"
                 : "+f"(c[0]), "+f"(c[1]), "+f"(c[2]), "+f"(c[3])
                 : "r"(a[0]), "r"(a[1]), "r"(a[2]), "r"(a[3]), "r"(b0), "r"(b1));
}
__device__ __forceinline__ uint4 lds128(uint32_t a) {
    uint4 v;
    asm volatile("ld.shared.v4.u32 {%0,%1,%2,%3}, [%4];" : "=r"(v.x), "=r"(v.y), "=r"(v.z), "=r"(v.w) : "r"(a) : "memory");
    return v;
}
__device__ __forceinline__ float4 lds128f(uint32_t a) {
    float4 v;
    asm volatile("ld.shared.v4.f32 {%0,%1,%2,%3}, [%4];" : "=f"(v.x), "=f"(v.y), "=f"(v.z), "=f"(v.w) : "r"(a) : "memory");
    return v;
}
__device__ __forceinline__ float2 lds64f(uint32_t a) {
    float2 v;
    asm volatile("ld.shared.v2.f32 {%0,%1}, [%2];" : "=f"(v.x), "=f"(v.y) : "r"(a) : "memory");
    return v;
}
__device__ __forceinline__ uint32_t lds32v(uint32_t a) {
    uint32_t v;
    asm volatile("ld.volatile.shared.u32 %0, [%1];" : "=r"(v) : "r"(a) : "memory");
    return v;
}
__device__ __forceinline__ void sts128(uint32_t a, uint4 v) {
    asm volatile("st.shared.v4.u32 [%0], {%1,%2,%3,%4};" ::"r"(a), "r"(v.x), "r"(v.y), "r"(v.z), "r"(v.w) : "memory");
}
__device__ __forceinline__ void sts64(uint32_t a, uint32_t x, uint32_t y) {
    asm volatile("st.shared.v2.u32 [%0], {%1,%2};" ::"r"(a), "r"(x), "r"(y) : "memory");
}
__device__ __forceinline__ void sts32(uint32_t a, uint32_t x) {
    asm volatile("st.volatile.shared.u32 [%0], %1;" ::"r"(a), "r"(x) : "memory");
}
__device__ __forceinline__ void poll128(uint4& v, const void* p, bool pred) {
    asm volatile("{\n .reg .pred p;\n setp.ne.u32 p, %5, 0;\n @p ld.relaxed.gpu.global.v4.u32 {%0,%1,%2,%3}, [%4];\n}"
                 : "+r"(v.x), "+r"(v.y), "+r"(v.z), "+r"(v.w) : "l"(p), "r"((uint32_t)pred) : "memory");
}
__device__ __forceinline__ void stg128(void* p, uint4 v) {
    asm volatile("st.relaxed.gpu.global.v4.u32 [%0], {%1,%2,%3,%4};" ::"l"(p), "r"(v.x), "r"(v.y), "r"(v.z), "r"(v.w) : "memory");
}
__device__ __forceinline__ void stg64(void* p, uint32_t x, uint32_t y) {
    asm volatile("st.relaxed.gpu.global.v2.u32 [%0], {%1,%2};" ::"l"(p), "r"(x), "r"(y) : "memory");
}
__device__ __forceinline__ void stg32(void* p, uint32_t x) {
    asm volatile("st.relaxed.gpu.global.u32 [%0], %1;" ::"l"(p), "r"(x) : "memory");
}
__device__ __forceinline__ uint32_t nz(float f) {
    uint32_t u = __float_as_uint(f);
    return u == 0u ? 0x80000000u : u;
}
__device__ __forceinline__ bool all_set(const uint4& v) { return v.x != 0u && v.y != 0u && v.z != 0u && v.w != 0u; }
__device__ __forceinline__ void poll2(uint4& a, const void* pa, uint4& b, const void* pb, int sleep_ns) {
    uint32_t n = 0;
    while (true) {
        const bool ma = !all_set(a), mb = !all_set(b);
        if (!__any_sync(0xffffffffu, ma || mb)) break;
        if (sleep_ns && n) __nanosleep(sleep_ns);
        poll128(a, pa, ma);
        poll128(b, pb, mb);
        if (++n > SPIN_LIMIT) __trap();
    }
}
__device__ __forceinline__ uint32_t pack_bf16(float lo, float hi) {
    uint32_t r;
    asm("cvt.rn.bf16x2.f32 %0, %1, %2;" : "=r"(r) : "f"(hi), "f"(lo));
    return r;
}
__device__ __forceinline__ float ex2(float x) {
    float r;
    asm("ex2.approx.ftz.f32 %0, %1;" : "=f"(r) : "f"(x));
    return r;
}
__device__ __forceinline__ float sel4(const float (&c)[4], int j) {
    float a = (j & 1) ? c[1] : c[0];
    float b = (j & 1) ? c[3] : c[2];
    return (j & 2) ? b : a;
}
__device__ __forceinline__ bool elect_one() {
    uint32_t p;
    asm volatile("{\n .reg .pred p;\n elect.sync _|p, 0xffffffff;\n selp.u32 %0, 1, 0, p;\n}" : "=r"(p));
    return p != 0;
}
__device__ __forceinline__ void bar_consumers() { asm volatile("bar.sync 1, 256;" ::: "memory"); }

__global__ void __launch_bounds__(NTHREADS, 1)
gqa2_decode_kernel(const __grid_constant__ Params prm) {
    extern __shared__ unsigned char smem_raw[];
    const uint32_t sb = ((uint32_t)__cvta_generic_to_shared(smem_raw) + 1023u) & ~1023u;
    const int tid = threadIdx.x, warp = tid >> 5, lane = tid & 31;
    const int bid = blockIdx.x, prob = bid >> 6, c = bid & 63;
    const uint32_t bar_full = sb + SM_BAR, bar_wo = bar_full + 16 * NST, bar_empty = bar_wo + 32;
    const uint32_t bar_ready = bar_empty + 8 * NST, bar_x = bar_ready + 8, bar_of = bar_ready + 16,
                   bar_go = bar_ready + 24, bar_ofa = bar_ready + 56, bar_gd = bar_ready + 64;

    int wu = __shfl_sync(0xffffffffu, warp, 0);
    if (wu == 8) {
        uint64_t pol;
        asm volatile("createpolicy.fractional.L2::evict_first.b64 %0, 1.0;" : "=l"(pol));
        if (elect_one()) {
#pragma unroll
            for (int s = 0; s < 2 * NST; s++) mbar_init(bar_full + 8 * s, 1);
            asm volatile("fence.mbarrier_init.release.cluster;" ::: "memory");
#pragma unroll
            for (int n = 0; n < DEPTH; n++) {
                mbar_expect(bar_full + 8 * n, 12288);
                tma4d(sb + SM_RING + (n >> 1) * TILE + (n & 1) * 12288, &prm.tm[prob][0], c * 64, n * 96, 0, bar_full + 8 * n, pol);
            }
#pragma unroll
            for (int s = 0; s < 4; s++) mbar_init(bar_wo + 8 * s, 1);
#pragma unroll
            for (int s = 0; s < NST; s++) mbar_init(bar_empty + 8 * s, 8);
#pragma unroll
            for (int s = 0; s < 7; s++) mbar_init(bar_ready + 8 * s, s == 2 ? 2 : 1);
            mbar_init(bar_ofa, 6);
            mbar_init(bar_gd, 9);
            asm volatile("fence.mbarrier_init.release.cluster;" ::: "memory");
            mbar_expect(bar_x, 1152);
            asm volatile("cp.async.bulk.shared::cluster.global.mbarrier::complete_tx::bytes [%0], [%1], 1152, [%2];"
                         ::"r"(sb + SM_X), "l"(prm.x[prob]), "r"(bar_x) : "memory");
            sts64(sb + SM_PROG, 0u, 0u);
#pragma unroll
            for (int k = 1; k < 4; k++) asm volatile("prefetch.tensormap [%0];" ::"l"(&prm.tm[prob][k]) : "memory");
        }
        __syncwarp();
        asm volatile("bar.arrive 3, %0;" ::"n"(NTHREADS) : "memory");
        int ib = DEPTH, iph = 0;
        int nw = 0, wb = 0, wph = 0;
#pragma unroll 1
        for (int n = DEPTH; n < 70; n++) {
            const bool kv = n >= 6;
            const int bytes = kv ? TILE / 2 : 12288;
            const uint32_t dst = sb + SM_RING + (ib >> 1) * TILE + (ib & 1) * bytes, bar = bar_full + 8 * ib;
            if (n >= 2 * NST && (n & 1) == 0) mbar_wait(bar_empty + 4 * ib, iph ^ 1);
            if (elect_one()) mbar_expect(bar, bytes);
            while (true) {
                int win = DEPTH;
                if (n >= 10) {
                    const int lag = (int)(lds32v(sb + SM_PROG) & 8191u) - ((n - 6) * 128 - 320);
                    win = min(max(DEPTH + (lag >> 7), 2), 8);
                }
                if (n - nw < win) break;
                mbar_wait(bar_full + 8 * wb, wph);
                nw++;
                if (++wb == 2 * NST) { wb = 0; wph ^= 1; }
            }
            if (elect_one()) {
                tma4d(dst, &prm.tm[prob][kv + (n >= 38)], kv ? 0 : c * 64, kv ? 0 : n * 96, kv ? (((n - 6) & 31) >> 2) * 2048 + (c >> 5) * 1024 + ((n - 6) & 3) * 256 + (c & 31) * 8 : 0, bar, pol);
                if (kv) sts32(sb + SM_PROG + 4, n - 5);
            }
            if (++ib == 2 * NST) { ib = 0; iph ^= 1; }
        }
#pragma unroll
        for (int k = 0; k < 4; k++) {
            if (k == 0) mbar_wait(bar_empty + 40, 0);
            else if (k < 3) mbar_wait(bar_empty + 8 * (k - 1), 1);
            mbar_wait(bar_full + 8 * ((70 + k - DEPTH) % 12), ((70 + k - DEPTH) / 12) & 1);
            if (elect_one())
                tma4d(sb + SM_RING + (k ? (k - 1) * 18432 : 5 * TILE), &prm.tm[prob][3], 0, (k * 1024 + ((c >> 4) & 1) * 512 + (c >> 5) * 256 + (c & 15) * 16) * 9, 0, bar_wo + 8 * k, pol);
        }
    } else {
        asm volatile("bar.sync 3, %0;" ::"n"(NTHREADS) : "memory");
    }
    asm volatile("" : "+r"(wu));
    const int g8 = lane >> 2, j4 = lane & 3, l8 = lane & 7, m4 = lane >> 3;
    const uint4 zero4 = make_uint4(0u, 0u, 0u, 0u);

    if (wu > 8) {
      if (wu < 11) {
        const int hf = wu - 9;
        float4* const psrc = g_s.part + bid * 512 + hf * 64 + lane;
#pragma unroll
        for (int i = 0; i < 8; i++) stg128(psrc + (i >> 1) * 128 + (i & 1) * 32, zero4);
#pragma unroll
        for (int i = 0; i < 2; i++) stg128(g_s.out + bid * 144 + (2 * hf + i) * 32 + lane, zero4);
        if (hf == 0) { if (lane < 16) stg128(g_s.out + bid * 144 + 128 + lane, zero4); }
        else if (lane < 8) stg128(g_s.stat + bid * 8 + lane, zero4);
        asm volatile("bar.sync 2, 64;" ::: "memory");
        if (tid == 288) {
            unsigned int v, n = 0;
            asm volatile("atom.release.gpu.global.add.u32 %0, [%1], 1;" : "=r"(v) : "l"(g_s.cnt + prob * 32) : "memory");
            const unsigned int target = (v & ~63u) + 64u;
            do {
                __nanosleep(5000);
                asm volatile("ld.relaxed.gpu.global.u32 %0, [%1];" : "=r"(v) : "l"(g_s.cnt + prob * 32) : "memory");
                if (++n > SPIN_LIMIT) __trap();
            } while ((int)(v - target) < 0);
            asm volatile("ld.acquire.gpu.global.u32 %0, [%1];" : "=r"(v) : "l"(g_s.cnt + prob * 32) : "memory");
            mbar_arrive(bar_ready);
        }
        __syncwarp();
        mbar_wait(bar_go, 0);
        float e0, e1;
        {
            uint4 sa = zero4, sc = zero4;
            const float4* ssrc = g_s.stat + (((bid >> 5) * 2 + ((c >> 3) & 1)) * 8 + 2 * m4 + ((c >> 4) & 1)) * 16 + l8;
            poll2(sa, ssrc + 8 * hf, sc, ssrc + 8 * (1 - hf), 300);
            if (hf == 0 && lane < 8) stg128(g_s.q + (prob * 16 + ((c >> 2) & 7) * 2 + (c >> 5)) * 32 + (c & 3) * 8 + lane, zero4);
            const float m0 = __uint_as_float(sa.x), m1 = __uint_as_float(sa.z), m2 = __uint_as_float(sc.x), m3 = __uint_as_float(sc.z);
            float M = fmaxf(fmaxf(m0, m1), fmaxf(m2, m3));
#pragma unroll
            for (int o = 4; o > 0; o >>= 1) M = fmaxf(M, __shfl_xor_sync(0xffffffffu, M, o));
            e0 = ex2(m0 - M); e1 = ex2(m1 - M);
            float L = (e0 * __uint_as_float(sa.y) + e1 * __uint_as_float(sa.w)) + (ex2(m2 - M) * __uint_as_float(sc.y) + ex2(m3 - M) * __uint_as_float(sc.w));
#pragma unroll
            for (int o = 4; o > 0; o >>= 1) L += __shfl_xor_sync(0xffffffffu, L, o);
            const float inv = 1.0f / L;
            e0 *= inv; e1 *= inv;
        }
        const bool up = lane >= 16;
        const int pr = 2 * j4 + (up ? 1 : 0);
        const uint32_t of_addr = sb + SM_OF + hf * 128 + ((pr & 3) * 8 + (pr >> 2)) * 4;
#pragma unroll 1
        for (int t = 0; t < 4; t++) {
            const float a0 = __shfl_sync(0xffffffffu, e0, 8 * t + (g8 >> 1)), a1 = __shfl_sync(0xffffffffu, e1, 8 * t + (g8 >> 1));
            const float b0 = __shfl_sync(0xffffffffu, e0, 8 * t + 4 + (g8 >> 1)), b1 = __shfl_sync(0xffffffffu, e1, 8 * t + 4 + (g8 >> 1));
            const float w0 = (g8 & 1) ? a1 : a0, w1 = (g8 & 1) ? b1 : b0;
            mbar_wait(bar_go + 8 * t, 0);
            uint4 pa = zero4, pb = zero4;
            poll2(pa, psrc + 128 * t, pb, psrc + 128 * t + 32, t < 3 ? 300 : 0);
            const float x = w0 * __uint_as_float(pa.x) + w1 * __uint_as_float(pb.x), y = w0 * __uint_as_float(pa.y) + w1 * __uint_as_float(pb.y);
            const float z = w0 * __uint_as_float(pa.z) + w1 * __uint_as_float(pb.z), w = w0 * __uint_as_float(pa.w) + w1 * __uint_as_float(pb.w);
            float k0 = (up ? z : x) + __shfl_xor_sync(0xffffffffu, up ? x : z, 16);
            float k1 = (up ? w : y) + __shfl_xor_sync(0xffffffffu, up ? y : w, 16);
#pragma unroll
            for (int o = 8; o > 2; o >>= 1) {
                k0 += __shfl_xor_sync(0xffffffffu, k0, o);
                k1 += __shfl_xor_sync(0xffffffffu, k1, o);
            }
            if ((lane & 12) == 0) sts32(of_addr + 8 * t, pack_bf16(k0, k1));
            __syncwarp();
            if (lane == 0) mbar_arrive(t < 3 ? bar_ofa : bar_of);
        }
        if (wu == 9) return;
      }
        if (wu == 11 && lane < 4) mbar_expect(bar_wo + 8 * lane, 18432);
        if (wu == 12) {
            if (lane == 0) {
                uint32_t rep = 0, n = 0;
                while (rep < 64u) {
                    const uint32_t cur = lds32v(sb + SM_PROG + 4);
                    if (cur == rep) { __nanosleep(40); if (++n > SPIN_LIMIT) __trap(); continue; }
                    uint32_t v;
                    asm volatile("atom.relaxed.gpu.global.add.u32 %0, [%1], %2;" : "=r"(v) : "l"(g_s.cnt + 64), "r"(cur - rep) : "memory");
                    sts32(sb + SM_PROG, v);
                    rep = cur;
                }
            }
            __syncwarp();
        }
        const int u = (wu - 10) * 64 + c;
        if (u >= 144) return;
        const float4* const osrc = g_s.out + (prob * 64 + lane) * 144 + u;
        const bool up = lane >= 16;
        uint32_t* const optr = reinterpret_cast<uint32_t*>(prm.out + prob * 576 + 16 * (u >> 2) + 2 * (u & 3) + (up ? 8 : 0));
        mbar_wait(bar_gd, 0);
        uint4 a = zero4, b = zero4;
        poll2(a, osrc, b, osrc + 32 * 144, 0);
        const float x = __uint_as_float(a.x) + __uint_as_float(b.x), y = __uint_as_float(a.y) + __uint_as_float(b.y);
        const float z = __uint_as_float(a.z) + __uint_as_float(b.z), w = __uint_as_float(a.w) + __uint_as_float(b.w);
        float k0 = (up ? y : x) + __shfl_xor_sync(0xffffffffu, up ? x : y, 16);
        float k1 = (up ? w : z) + __shfl_xor_sync(0xffffffffu, up ? z : w, 16);
#pragma unroll
        for (int o = 8; o > 0; o >>= 1) {
            k0 += __shfl_xor_sync(0xffffffffu, k0, o);
            k1 += __shfl_xor_sync(0xffffffffu, k1, o);
        }
        if ((lane & 15) == 0) *optr = pack_bf16(k0, k1);
        return;
    } else if (wu < 8) {
        {
            uint32_t xb[3][12];
            mbar_wait(bar_x, 0);
#pragma unroll
            for (int b = 0; b < 3; b++)
#pragma unroll
                for (int t = 0; t < 12; t++) xb[b][t] = lds32v(sb + SM_X + ((warp >> 2) * 48 + j4 + b * 96 + 4 * t) * 4);
            float c0[4] = {0.f, 0.f, 0.f, 0.f}, c1[4] = {0.f, 0.f, 0.f, 0.f};
            const uint32_t base = sb + SM_RING + ((warp >> 2) * 96 + (m4 >> 1) * 8 + l8) * 128 + (((2 * (warp & 3) + (m4 & 1)) ^ l8) << 4);
#pragma unroll
            for (int b = 0; b < 3; b++) {
                mbar_wait(bar_full + 16 * b + 8 * (warp >> 2), 0);
#pragma unroll
                for (int t = 0; t < 3; t++) {
                    uint32_t a0[4], a1[4];
                    ldsm4t(a0, base + b * TILE + (2 * t) * 2048);
                    ldsm4t(a1, base + b * TILE + (2 * t + 1) * 2048);
                    mma16816(c0, a0, xb[b][4 * t], xb[b][4 * t + 1]);
                    mma16816(c1, a1, xb[b][4 * t + 2], xb[b][4 * t + 3]);
                }
                __syncwarp();
                if (lane == 0) mbar_arrive(bar_empty + 8 * b);
            }
            if (j4 < 2) sts32(sb + SM_RED + (warp * 16 + g8 + 8 * j4) * 4, __float_as_uint(j4 ? c0[2] + c1[2] : c0[0] + c1[0]));
        }
        bar_consumers();
        if (warp == 0) {
            const float2 va = lds64f(sb + SM_RED + lane * 8), vb = lds64f(sb + SM_RED + 256 + lane * 8);
            uint32_t u = pack_bf16(va.x + vb.x, va.y + vb.y);
            if (u == 0u) u = 0x8000u;
            const int d = 64 * (c & 1) + 2 * lane;
            const int w16 = 2 * (d >> 4) + ((d >> 3) & 1);
            stg32(reinterpret_cast<uint32_t*>(g_s.q) + (bid >> 2) * 128 + (w16 >> 2) * 32 + ((c >> 1) & 1) * 16 + ((d & 7) >> 1) * 4 + (w16 & 3), u);
        }
        {
            uint4 v = zero4, dummy = make_uint4(1u, 1u, 1u, 1u);
            mbar_wait(bar_full + 8 * 8, 0);
            poll2(v, g_s.q + (prob * 16 + warp * 2 + (c >> 5)) * 32 + lane, dummy, g_s.q, 300);
            sts128(sb + SM_Q + warp * 512 + lane * 16, v);
        }
        bar_consumers();
        const uint32_t frag_off = (g8 & 1) * 64 + j4 * 16;
        int s = 3, ph = 0;

        {
            const uint32_t kbase = sb + SM_RING + (2 * warp + (m4 & 1)) * 2048 + l8 * 128 + (((m4 >> 1) ^ l8) << 4);
            const uint32_t sc_addr = sb + SM_SC + (warp * 32 + (j4 & 1) * 16 + (g8 >> 1) * 4 + (g8 & 1) + (j4 >> 1) * 2) * 4;
            uint4 qb[4];
#pragma unroll 1
            for (int i = 0; i < 16; i++) {
                if ((i & 1) == 0) {
#pragma unroll
                    for (int q = 0; q < 4; q++) qb[q] = lds128(sb + SM_Q + (i >> 1) * 512 + q * 128 + frag_off);
                }
                mbar_wait(bar_full + 16 * s + 8 * (warp >> 2), ph);
                float c0[4] = {0.f, 0.f, 0.f, 0.f}, c1[4] = {0.f, 0.f, 0.f, 0.f};
                const uint32_t kb = kbase + s * TILE;
#pragma unroll
                for (int q = 0; q < 4; q++) {
                    uint32_t a0[4], a1[4];
                    ldsm4(a0, (kb ^ (((2 * q) & 3) << 5)) + (q >> 1) * 1024);
                    ldsm4(a1, (kb ^ (((2 * q + 1) & 3) << 5)) + (q >> 1) * 1024);
                    mma16816(c0, a0, qb[q].x, qb[q].y);
                    mma16816(c1, a1, qb[q].z, qb[q].w);
                }
                __syncwarp();
                if (lane == 0) mbar_arrive(bar_empty + 8 * s);
                sts32(sc_addr + i * 1024, __float_as_uint(sel4(c0, j4) + sel4(c1, j4)));
                if (++s == NST) { s = 0; ph ^= 1; }
            }
        }
        mbar_wait(bar_ready, 0);
        bar_consumers();

        {
            constexpr float SCALE = 0.08838834764831845f * 1.4426950408889634f;
            const int hd = warp & 1, st = warp >> 1;
            float4 sv[4];
            float ms[2] = {-INFINITY, -INFINITY}, sum[2] = {0.f, 0.f};
#pragma unroll
            for (int t = 0; t < 4; t++) {
                sv[t] = lds128f(sb + SM_SC + ((4 * st + t) * 256 + g8 * 32 + hd * 16 + j4 * 4) * 4);
                ms[t >> 1] = fmaxf(ms[t >> 1], fmaxf(fmaxf(sv[t].x, sv[t].y), fmaxf(sv[t].z, sv[t].w)));
            }
#pragma unroll
            for (int o = 16; o > 0; o >>= 1) {
                ms[0] = fmaxf(ms[0], __shfl_xor_sync(0xffffffffu, ms[0], o));
                ms[1] = fmaxf(ms[1], __shfl_xor_sync(0xffffffffu, ms[1], o));
            }
            ms[0] *= SCALE; ms[1] *= SCALE;
#pragma unroll
            for (int t = 0; t < 4; t++) {
                const float m = ms[t >> 1];
                const float p0 = ex2(fmaf(sv[t].x, SCALE, -m)), p1 = ex2(fmaf(sv[t].y, SCALE, -m));
                const float p2 = ex2(fmaf(sv[t].z, SCALE, -m)), p3 = ex2(fmaf(sv[t].w, SCALE, -m));
                sum[t >> 1] += (p0 + p1) + (p2 + p3);
                sts64(sb + SM_P + (4 * st + t) * 512 + (g8 >> 1) * 128 + hd * 64 + j4 * 16 + (g8 & 1) * 8, pack_bf16(p0, p1), pack_bf16(p2, p3));
            }
            bar_consumers();
#pragma unroll
            for (int o = 16; o > 0; o >>= 1) {
                sum[0] += __shfl_xor_sync(0xffffffffu, sum[0], o);
                sum[1] += __shfl_xor_sync(0xffffffffu, sum[1], o);
            }
            if (lane < 2)
                stg64(reinterpret_cast<float2*>(g_s.stat) + (((bid >> 5) * 2 + hd) * 8 + 2 * st + lane) * 32 + (c & 31),
                      nz(lane ? ms[1] : ms[0]), nz(lane ? sum[1] : sum[0]));
        }

        {
            const uint32_t vbase = sb + SM_RING + (m4 >> 1) * 2048 + (warp >> 2) * 1024 + l8 * 128 + (((2 * (warp & 3) + (m4 & 1)) ^ l8) << 4);
            float* const dst = reinterpret_cast<float*>(g_s.part) + ((bid & ~31) + 8 * (j4 & 1) + warp) * 2048 + (c & 31) * 16 + g8 + 8 * (j4 >> 1);
            const int go_off = 3 + 2 * ((c >> 4) & 1);
            float c0[4] = {0.f, 0.f, 0.f, 0.f}, c1[4] = {0.f, 0.f, 0.f, 0.f};
#pragma unroll 1
            for (int i = 0; i < 16; i++) {
                uint4 pb[4];
#pragma unroll
                for (int q = 0; q < 4; q++) pb[q] = lds128(sb + SM_P + i * 512 + q * 128 + frag_off);
                const uint32_t vb = vbase + s * TILE;
#pragma unroll
                for (int q = 0; q < 4; q++) {
                    uint32_t a0[4], a1[4];
                    if ((q & 1) == 0) mbar_wait(bar_full + 16 * s + 4 * q, ph);
                    ldsm4t(a0, vb + (2 * q) * 4096);
                    ldsm4t(a1, vb + (2 * q + 1) * 4096);
                    mma16816(c0, a0, pb[q].x, pb[q].y);
                    mma16816(c1, a1, pb[q].z, pb[q].w);
                }
                __syncwarp();
                if (lane == 0) mbar_arrive(bar_empty + 8 * s);
                if (i & 1) {
                    stg32(dst + ((i >> 1) & 1) * (16 * 2048) + (i >> 2) * 512, nz(sel4(c0, j4) + sel4(c1, j4)));
#pragma unroll
                    for (int e = 0; e < 4; e++) { c0[e] = 0.f; c1[e] = 0.f; }
                }
                if (tid == 0 && (i == 15 || (i >= go_off && ((i - go_off) & 3) == 0))) mbar_arrive(bar_go + (i == 15 ? 24 : 2 * (i - go_off)));
                if (++s == NST) { s = 0; ph ^= 1; }
            }
        }
    }

    {
        float acc[2][4][4];
#pragma unroll
        for (int e = 0; e < 32; e++) (&acc[0][0][0])[e] = 0.f;
        const int rho = 9 * ((m4 >> 1) * 8 + l8) + warp;
        uint32_t base[4];
#pragma unroll
        for (int mt = 0; mt < 4; mt++) base[mt] = (sb + SM_RING + rho * 128 + (((m4 & 1) ^ (rho & 7)) << 4)) ^ (mt << 5);
        float* dst = reinterpret_cast<float*>(g_s.out) + bid * 576 + warp * 64 + 16 * j4 + 2 * g8;
        uint32_t js = j4, of_addr = sb + SM_OF + (g8 & 1) * 128 + j4 * 32;
        asm volatile("" : "+r"(base[0]), "+r"(base[1]), "+r"(base[2]), "+r"(base[3]), "+l"(dst), "+r"(js), "+r"(of_addr));
        uint32_t wa[2][4][4];
#define LOAD_W(t) _Pragma("unroll") for (int mt = 0; mt < 4; mt++) ldsm4t(wa[(t) & 1][mt], base[mt] + ((t) ? ((t) - 1) * 18432 : 5 * TILE))
#define MMA_W(t, b0, b1) _Pragma("unroll") for (int mt = 0; mt < 4; mt++) mma16816(acc[(t) & 1][mt], wa[(t) & 1][mt], b0, b1)
        auto pick = [&](int a, int e) {
            float r;
            asm("{\n .reg .pred p, q;\n .reg .f32 u, v;\n .reg .b32 t;\n and.b32 t, %5, 1;\n setp.ne.u32 p, t, 0;\n setp.gt.u32 q, %5, 1;\n"
                " selp.f32 u, %2, %1, p;\n selp.f32 v, %4, %3, p;\n selp.f32 %0, v, u, q;\n}"
                : "=f"(r) : "f"(acc[a][0][e]), "f"(acc[a][1][e]), "f"(acc[a][2][e]), "f"(acc[a][3][e]), "r"(js));
            return r;
        };
        mbar_wait(bar_ofa, 0);
        const uint4 o0 = lds128(of_addr);
        const float2 o1 = lds64f(of_addr + 16);
        mbar_wait(bar_wo, 0);
        LOAD_W(0);
        MMA_W(0, o0.x, o0.y);
        mbar_wait(bar_wo + 8, 0);
        LOAD_W(1);
        MMA_W(1, o0.z, o0.w);
        mbar_wait(bar_wo + 16, 0);
        LOAD_W(2);
        const bool have_w = mbar_test(bar_wo + 24, 0);
        if (have_w) { LOAD_W(3); }
        MMA_W(2, __float_as_uint(o1.x), __float_as_uint(o1.y));
        float2 o2;
        bool have_o = false;
        if (!have_w) {
            uint32_t n = 0;
            while (!mbar_test(bar_wo + 24, 0)) {
                if (mbar_test(bar_of, 0)) {
                    o2 = lds64f(of_addr + 24);
                    have_o = true;
                    mbar_wait(bar_wo + 24, 0);
                    break;
                }
                if (++n > (SPIN_LIMIT << 4)) __trap();
            }
            LOAD_W(3);
        }
        if (!have_o) { mbar_wait(bar_of, 0); o2 = lds64f(of_addr + 24); }
        MMA_W(3, __float_as_uint(o2.x), __float_as_uint(o2.y));
        stg64(dst, nz((pick(0, 0) + pick(0, 1)) + (pick(1, 0) + pick(1, 1))), nz((pick(0, 2) + pick(0, 3)) + (pick(1, 2) + pick(1, 3))));
        if (lane == 0) mbar_arrive(bar_gd);
#undef LOAD_W
#undef MMA_W
    }
}

typedef CUresult (*EncodeFn)(CUtensorMap*, CUtensorMapDataType, cuuint32_t, void*, const cuuint64_t*, const cuuint64_t*,
                             const cuuint32_t*, const cuuint32_t*, CUtensorMapInterleave, CUtensorMapSwizzle,
                             CUtensorMapL2promotion, CUtensorMapFloatOOBfill);

}

extern "C" void kernel_launch(void* const* d_in, const int* in_sizes, int n_in, void* d_out, int out_size) {
    (void)in_sizes; (void)n_in; (void)out_size;
    static EncodeFn enc = nullptr;
    if (!enc) {
        cudaDriverEntryPointQueryResult qr;
        void* fn = nullptr;
        cudaGetDriverEntryPoint("cuTensorMapEncodeTiled", &fn, cudaEnableDefault, &qr);
        enc = (EncodeFn)fn;
        cudaFuncSetAttribute(gqa2_decode_kernel, cudaFuncAttributeMaxDynamicSharedMemorySize, SM_TOTAL);
    }
    Params prm;
    const cuuint32_t es[4] = {1, 1, 1, 1};
    for (int p = 0; p < 2; p++) {
        prm.x[p] = (const __nv_bfloat16*)d_in[5 * p + 0];
        void* ptr[4] = {d_in[5 * p + 3], d_in[5 * p + 1], d_in[5 * p + 2], d_in[5 * p + 4]};
        const cuuint64_t gd[4][4] = {{4096, 576, 1, 1}, {64, 8, 2, 16 * 8192 / 8}, {64, 8, 2, 16 * 8192 / 8}, {64, 4096 * 9, 1, 1}};
        const cuuint64_t gs[4][3] = {{8192, 8192 * 576, 8192 * 576}, {256, 128, 2048}, {256, 128, 2048}, {128, 128 * 4096 * 9, 128 * 4096 * 9}};
        const cuuint32_t bd[4][4] = {{64, 96, 1, 1}, {64, 8, 2, 8}, {64, 8, 2, 8}, {64, 144, 1, 1}};
        for (int i = 0; i < 4; i++)
            enc(&prm.tm[p][i], CU_TENSOR_MAP_DATA_TYPE_BFLOAT16, 4, ptr[i], gd[i], gs[i], bd[i], es,
                CU_TENSOR_MAP_INTERLEAVE_NONE, CU_TENSOR_MAP_SWIZZLE_128B, CU_TENSOR_MAP_L2_PROMOTION_L2_128B,
                CU_TENSOR_MAP_FLOAT_OOB_FILL_NONE);
    }
    prm.out = (__nv_bfloat16*)d_out;
    gqa2_decode_kernel<<<128, NTHREADS, SM_TOTAL>>>(prm);
}
```

```cpp
#include <cuda_runtime.h>
#include <cuda_bf16.h>
#include <cuda.h>
#include <stdint.h>

namespace {

constexpr int TILE = 32768;
constexpr int NST  = 6;
constexpr int DEPTH = 4;
constexpr int NTHREADS = 416;

constexpr int SM_RING = 0;
constexpr int SM_SC   = NST * TILE;
constexpr int SM_P    = SM_SC + 16384;
constexpr int SM_Q    = SM_P;
constexpr int SM_X    = SM_P + 8192;
constexpr int SM_RED  = SM_X + 1152;
constexpr int SM_OF   = SM_RED + 512;
constexpr int SM_PROG = SM_OF + 256;
constexpr int SM_BAR  = SM_PROG + 16;
constexpr int SM_TOTAL = SM_BAR + 320 + 1024;

struct alignas(64) Params {
    CUtensorMap tm[2][4];
    const __nv_bfloat16* x[2];
    __nv_bfloat16* out;
};

struct alignas(4096) Scratch {
    float4 out[128 * 144];
    float4 part[128 * 1024];
    uint4  q[128 * 8];
    float4 stat[128 * 16];
    unsigned int cnt[3 * 32];
};
__device__ Scratch g_s;

constexpr uint32_t SPIN_LIMIT = 1u << 22;

__device__ __forceinline__ void mbar_init(uint32_t a, uint32_t c) {
    asm volatile("mbarrier.init.shared::cta.b64 [%0], %1;" ::"r"(a), "r"(c) : "memory");
}
__device__ __forceinline__ void mbar_expect(uint32_t a, uint32_t b) {
    asm volatile("mbarrier.arrive.expect_tx.shared::cta.b64 _, [%0], %1;" ::"r"(a), "r"(b) : "memory");
}
__device__ __forceinline__ void mbar_arrive(uint32_t a) {
    asm volatile("mbarrier.arrive.shared::cta.b64 _, [%0];" ::"r"(a) : "memory");
}
__device__ __forceinline__ void mbar_wait(uint32_t a, uint32_t ph) {
    uint32_t ok, n = 0;
    do {
        asm volatile("{\n .reg .pred p;\n mbarrier.try_wait.parity.shared::cta.b64 p, [%1], %2;\n selp.u32 %0, 1, 0, p;\n}"
                     : "=r"(ok) : "r"(a), "r"(ph) : "memory");
        if (++n > SPIN_LIMIT) __trap();
    } while (!ok);
}
__device__ __forceinline__ bool mbar_test(uint32_t a, uint32_t ph) {
    uint32_t ok;
    asm volatile("{\n .reg .pred p;\n mbarrier.test_wait.parity.shared::cta.b64 p, [%1], %2;\n selp.u32 %0, 1, 0, p;\n}"
                 : "=r"(ok) : "r"(a), "r"(ph) : "memory");
    return __all_sync(0xffffffffu, ok != 0);
}
__device__ __forceinline__ void tma4d(uint32_t dst, const CUtensorMap* tm, int c0, int c1, int c3, uint32_t mbar, uint64_t pol) {
    asm volatile("cp.async.bulk.tensor.4d.shared::cluster.global.mbarrier::complete_tx::bytes.L2::cache_hint"
                 " [%0], [%1, {%3, %4, %5, %6}], [%2], %7;"
                 ::"r"(dst), "l"(tm), "r"(mbar), "r"(c0), "r"(c1), "r"(0), "r"(c3), "l"(pol) : "memory");
}
__device__ __forceinline__ void ldsm4(uint32_t (&r)[4], uint32_t a) {
    asm volatile("ldmatrix.sync.aligned.m8n8.x4.shared.b16 {%0,%1,%2,%3}, [%4];"
                 : "=r"(r[0]), "=r"(r[1]), "=r"(r[2]), "=r"(r[3]) : "r"(a) : "memory");
}
__device__ __forceinline__ void ldsm4t(uint32_t (&r)[4], uint32_t a) {
    asm volatile("ldmatrix.sync.aligned.m8n8.x4.trans.shared.b16 {%0,%1,%2,%3}, [%4];"
                 : "=r"(r[0]), "=r"(r[1]), "=r"(r[2]), "=r"(r[3]) : "r"(a) : "memory");
}
__device__ __forceinline__ void mma16816(float (&c)[4], const uint32_t (&a)[4], uint32_t b0, uint32_t b1) {
    asm volatile("mma.sync.aligned.m16n8k16.row.col.f32.bf16.bf16.f32 {%0,%1,%2,%3}, {%4,%5,%6,%7}, {%8,%9}, {%0,%1,%2,%3};"
                 : "+f"(c[0]), "+f"(c[1]), "+f"(c[2]), "+f"(c[3])
                 : "r"(a[0]), "r"(a[1]), "r"(a[2]), "r"(a[3]), "r"(b0), "r"(b1));
}
__device__ __forceinline__ uint4 lds128(uint32_t a) {
    uint4 v;
    asm volatile("ld.shared.v4.u32 {%0,%1,%2,%3}, [%4];" : "=r"(v.x), "=r"(v.y), "=r"(v.z), "=r"(v.w) : "r"(a) : "memory");
    return v;
}
__device__ __forceinline__ float4 lds128f(uint32_t a) {
    float4 v;
    asm volatile("ld.shared.v4.f32 {%0,%1,%2,%3}, [%4];" : "=f"(v.x), "=f"(v.y), "=f"(v.z), "=f"(v.w) : "r"(a) : "memory");
    return v;
}
__device__ __forceinline__ float2 lds64f(uint32_t a) {
    float2 v;
    asm volatile("ld.shared.v2.f32 {%0,%1}, [%2];" : "=f"(v.x), "=f"(v.y) : "r"(a) : "memory");
    return v;
}
__device__ __forceinline__ uint32_t lds32v(uint32_t a) {
    uint32_t v;
    asm volatile("ld.volatile.shared.u32 %0, [%1];" : "=r"(v) : "r"(a) : "memory");
    return v;
}
__device__ __forceinline__ void sts128(uint32_t a, uint4 v) {
    asm volatile("st.shared.v4.u32 [%0], {%1,%2,%3,%4};" ::"r"(a), "r"(v.x), "r"(v.y), "r"(v.z), "r"(v.w) : "memory");
}
__device__ __forceinline__ void sts64(uint32_t a, uint32_t x, uint32_t y) {
    asm volatile("st.shared.v2.u32 [%0], {%1,%2};" ::"r"(a), "r"(x), "r"(y) : "memory");
}
__device__ __forceinline__ void sts32(uint32_t a, uint32_t x) {
    asm volatile("st.volatile.shared.u32 [%0], %1;" ::"r"(a), "r"(x) : "memory");
}
__device__ __forceinline__ void poll128(uint4& v, const void* p, bool pred) {
    asm volatile("{\n .reg .pred p;\n setp.ne.u32 p, %5, 0;\n @p ld.relaxed.gpu.global.v4.u32 {%0,%1,%2,%3}, [%4];\n}"
                 : "+r"(v.x), "+r"(v.y), "+r"(v.z), "+r"(v.w) : "l"(p), "r"((uint32_t)pred) : "memory");
}
__device__ __forceinline__ void stg128(void* p, uint4 v) {
    asm volatile("st.relaxed.gpu.global.v4.u32 [%0], {%1,%2,%3,%4};" ::"l"(p), "r"(v.x), "r"(v.y), "r"(v.z), "r"(v.w) : "memory");
}
__device__ __forceinline__ void stg64(void* p, uint32_t x, uint32_t y) {
    asm volatile("st.relaxed.gpu.global.v2.u32 [%0], {%1,%2};" ::"l"(p), "r"(x), "r"(y) : "memory");
}
__device__ __forceinline__ void stg32(void* p, uint32_t x) {
    asm volatile("st.relaxed.gpu.global.u32 [%0], %1;" ::"l"(p), "r"(x) : "memory");
}
__device__ __forceinline__ uint32_t nz(float f) {
    uint32_t u = __float_as_uint(f);
    return u == 0u ? 0x80000000u : u;
}
__device__ __forceinline__ bool all_set(const uint4& v) { return v.x != 0u && v.y != 0u && v.z != 0u && v.w != 0u; }
__device__ __forceinline__ void poll2(uint4& a, const void* pa, uint4& b, const void* pb, int sleep_ns) {
    uint32_t n = 0;
    while (true) {
        const bool ma = !all_set(a), mb = !all_set(b);
        if (!__any_sync(0xffffffffu, ma || mb)) break;
        if (sleep_ns && n) __nanosleep(sleep_ns);
        poll128(a, pa, ma);
        poll128(b, pb, mb);
        if (++n > SPIN_LIMIT) __trap();
    }
}
__device__ __forceinline__ uint32_t pack_bf16(float lo, float hi) {
    uint32_t r;
    asm("cvt.rn.bf16x2.f32 %0, %1, %2;" : "=r"(r) : "f"(hi), "f"(lo));
    return r;
}
__device__ __forceinline__ float ex2(float x) {
    float r;
    asm("ex2.approx.ftz.f32 %0, %1;" : "=f"(r) : "f"(x));
    return r;
}
__device__ __forceinline__ float sel4(const float (&c)[4], int j) {
    float a = (j & 1) ? c[1] : c[0];
    float b = (j & 1) ? c[3] : c[2];
    return (j & 2) ? b : a;
}
__device__ __forceinline__ bool elect_one() {
    uint32_t p;
    asm volatile("{\n .reg .pred p;\n elect.sync _|p, 0xffffffff;\n selp.u32 %0, 1, 0, p;\n}" : "=r"(p));
    return p != 0;
}
__device__ __forceinline__ void bar_consumers() { asm volatile("bar.sync 1, 256;" ::: "memory"); }

__global__ void __launch_bounds__(NTHREADS, 1)
gqa2_decode_kernel(const __grid_constant__ Params prm) {
    extern __shared__ unsigned char smem_raw[];
    const uint32_t sb = ((uint32_t)__cvta_generic_to_shared(smem_raw) + 1023u) & ~1023u;
    const int tid = threadIdx.x, warp = tid >> 5, lane = tid & 31;
    const int bid = blockIdx.x, prob = bid >> 6, c = bid & 63;
    const uint32_t bar_full = sb + SM_BAR, bar_wo = bar_full + 16 * NST, bar_empty = bar_wo + 32;
    const uint32_t bar_ready = bar_empty + 8 * NST, bar_x = bar_ready + 8, bar_of = bar_ready + 16,
                   bar_go = bar_ready + 24, bar_ofa = bar_ready + 56, bar_gd = bar_ready + 64;

    int wu = __shfl_sync(0xffffffffu, warp, 0);
    if (wu == 8) {
        uint64_t pol;
        asm volatile("createpolicy.fractional.L2::evict_first.b64 %0, 1.0;" : "=l"(pol));
        if (elect_one()) {
#pragma unroll
            for (int s = 0; s < 2 * NST; s++) mbar_init(bar_full + 8 * s, 1);
            asm volatile("fence.mbarrier_init.release.cluster;" ::: "memory");
#pragma unroll
            for (int n = 0; n < DEPTH; n++) {
                mbar_expect(bar_full + 8 * n, 12288);
                tma4d(sb + SM_RING + (n >> 1) * TILE + (n & 1) * 12288, &prm.tm[prob][0], c * 64, n * 96, 0, bar_full + 8 * n, pol);
            }
#pragma unroll
            for (int s = 0; s < 4; s++) mbar_init(bar_wo + 8 * s, 1);
#pragma unroll
            for (int s = 0; s < NST; s++) mbar_init(bar_empty + 8 * s, 8);
#pragma unroll
            for (int s = 0; s < 7; s++) mbar_init(bar_ready + 8 * s, s == 2 ? 2 : 1);
            mbar_init(bar_ofa, 6);
            mbar_init(bar_gd, 9);
            asm volatile("fence.mbarrier_init.release.cluster;" ::: "memory");
            mbar_expect(bar_x, 1152);
            asm volatile("cp.async.bulk.shared::cluster.global.mbarrier::complete_tx::bytes [%0], [%1], 1152, [%2];"
                         ::"r"(sb + SM_X), "l"(prm.x[prob]), "r"(bar_x) : "memory");
            sts64(sb + SM_PROG, 0u, 0u);
#pragma unroll
            for (int k = 1; k < 4; k++) asm volatile("prefetch.tensormap [%0];" ::"l"(&prm.tm[prob][k]) : "memory");
        }
        __syncwarp();
        asm volatile("bar.arrive 3, %0;" ::"n"(NTHREADS) : "memory");
        int ib = DEPTH, iph = 0;
        int nw = 0, wb = 0, wph = 0;
#pragma unroll 1
        for (int n = DEPTH; n < 70; n++) {
            const bool kv = n >= 6;
            const int bytes = kv ? TILE / 2 : 12288;
            const uint32_t dst = sb + SM_RING + (ib >> 1) * TILE + (ib & 1) * bytes, bar = bar_full + 8 * ib;
            if (n >= 2 * NST && (n & 1) == 0) mbar_wait(bar_empty + 4 * ib, iph ^ 1);
            if (elect_one()) mbar_expect(bar, bytes);
            while (true) {
                int win = DEPTH;
                if (n >= 14) {
                    const int lag = (int)(lds32v(sb + SM_PROG) & 8191u) - ((n - 10) * 128 - 256);
                    win = min(max(DEPTH + (lag >> 7), 2), 8);
                }
                if (n - nw < win) break;
                mbar_wait(bar_full + 8 * wb, wph);
                nw++;
                if (++wb == 2 * NST) { wb = 0; wph ^= 1; }
            }
            if (elect_one()) {
                tma4d(dst, &prm.tm[prob][kv + (n >= 38)], kv ? 0 : c * 64, kv ? 0 : n * 96, kv ? ((n - 6) & 31) * 512 + c * 8 : 0, bar, pol);
                if (n >= 10) sts32(sb + SM_PROG + 4, n - 9);
            }
            if (++ib == 2 * NST) { ib = 0; iph ^= 1; }
        }
#pragma unroll
        for (int k = 0; k < 4; k++) {
            if (k == 0) mbar_wait(bar_empty + 40, 0);
            else if (k < 3) mbar_wait(bar_empty + 8 * (k - 1), 1);
            for (int w = 6; w >= 2; w--) {
                const int m = 70 + k - w;
                mbar_wait(bar_full + 8 * (m < 70 ? m - 60 : m - 58), m < 70 ? 1 : 0);
                const int lag = (int)(lds32v(sb + SM_PROG) & 8191u) - ((60 + k) * 128 - 256);
                if (w <= DEPTH + (lag >> 7)) break;
            }
            if (elect_one()) sts32(sb + SM_PROG + 4, 61 + k);
            if (elect_one())
                tma4d(sb + SM_RING + (k ? (k - 1) * 18432 : 5 * TILE), &prm.tm[prob][3], 0, (k * 1024 + c * 16) * 9, 0, bar_wo + 8 * k, pol);
        }
    } else {
        asm volatile("bar.sync 3, %0;" ::"n"(NTHREADS) : "memory");
    }
    asm volatile("" : "+r"(wu));
    const int g8 = lane >> 2, j4 = lane & 3, l8 = lane & 7, m4 = lane >> 3;
    const uint4 zero4 = make_uint4(0u, 0u, 0u, 0u);

    if (wu > 8) {
        if (wu < 11) {
            const int hf = wu - 9;
            float4* const psrc = g_s.part + bid * 1024 + hf * 128 + lane;
#pragma unroll
            for (int i = 0; i < 16; i++) { stg128(psrc + (i >> 2) * 256 + (i & 3) * 32, zero4); __nanosleep(300); }
#pragma unroll
            for (int i = 0; i < 2; i++) stg128(g_s.out + bid * 144 + (2 * hf + i) * 32 + lane, zero4);
            if (lane < 16) stg128(hf == 0 ? g_s.out + bid * 144 + 128 + lane : g_s.stat + bid * 16 + lane, zero4);
            asm volatile("bar.sync 2, 64;" ::: "memory");
            if (tid == 288) {
                unsigned int v, n = 0;
                asm volatile("atom.release.gpu.global.add.u32 %0, [%1], 1;" : "=r"(v) : "l"(g_s.cnt + prob * 32) : "memory");
                const unsigned int target = (v & ~63u) + 64u;
                do {
                    __nanosleep(n ? 1000 : 3000);
                    asm volatile("ld.relaxed.gpu.global.u32 %0, [%1];" : "=r"(v) : "l"(g_s.cnt + prob * 32) : "memory");
                    if (++n > SPIN_LIMIT) __trap();
                } while ((int)(v - target) < 0);
                asm volatile("ld.acquire.gpu.global.u32 %0, [%1];" : "=r"(v) : "l"(g_s.cnt + prob * 32) : "memory");
                mbar_arrive(bar_ready);
            }
            __syncwarp();
            mbar_wait(bar_go, 0);
            float e[4];
            {
                uint4 sa = zero4, sb2 = zero4, sc = zero4, sd = zero4;
                const float4* ssrc = g_s.stat + ((prob * 2 + ((c >> 3) & 1)) * 16 + 4 * m4 + (c >> 4)) * 32 + l8;
                poll128(sc, ssrc + 16 * (1 - hf), true);
                poll128(sd, ssrc + 16 * (1 - hf) + 8, true);
                poll2(sa, ssrc + 16 * hf, sb2, ssrc + 16 * hf + 8, 300);
                poll2(sc, ssrc + 16 * (1 - hf), sd, ssrc + 16 * (1 - hf) + 8, 300);
                if (hf == 0 && lane < 8) stg128(g_s.q + bid * 8 + lane, zero4);
                float M = fmaxf(fmaxf(fmaxf(__uint_as_float(sa.x), __uint_as_float(sa.z)), fmaxf(__uint_as_float(sb2.x), __uint_as_float(sb2.z))),
                                fmaxf(fmaxf(__uint_as_float(sc.x), __uint_as_float(sc.z)), fmaxf(__uint_as_float(sd.x), __uint_as_float(sd.z))));
#pragma unroll
                for (int o = 4; o > 0; o >>= 1) M = fmaxf(M, __shfl_xor_sync(0xffffffffu, M, o));
                e[0] = ex2(__uint_as_float(sa.x) - M); e[1] = ex2(__uint_as_float(sa.z) - M);
                e[2] = ex2(__uint_as_float(sb2.x) - M); e[3] = ex2(__uint_as_float(sb2.z) - M);
                const float La = (e[0] * __uint_as_float(sa.y) + e[1] * __uint_as_float(sa.w)) + (e[2] * __uint_as_float(sb2.y) + e[3] * __uint_as_float(sb2.w));
                const float Lb = (ex2(__uint_as_float(sc.x) - M) * __uint_as_float(sc.y) + ex2(__uint_as_float(sc.z) - M) * __uint_as_float(sc.w)) +
                                 (ex2(__uint_as_float(sd.x) - M) * __uint_as_float(sd.y) + ex2(__uint_as_float(sd.z) - M) * __uint_as_float(sd.w));
                float L = La + Lb;
#pragma unroll
                for (int o = 4; o > 0; o >>= 1) L += __shfl_xor_sync(0xffffffffu, L, o);
                const float inv = 1.0f / L;
#pragma unroll
                for (int i = 0; i < 4; i++) e[i] *= inv;
            }
            const bool up = lane >= 16;
            const int pr = 2 * j4 + (up ? 1 : 0);
            const uint32_t of_addr = sb + SM_OF + hf * 128 + ((pr & 3) * 8 + (pr >> 2)) * 4;
#pragma unroll 1
            for (int t = 0; t < 4; t++) {
                float wg[4];
#pragma unroll
                for (int i = 0; i < 4; i++) {
                    const float u0 = __shfl_sync(0xffffffffu, e[i & 2], 8 * t + 4 * (i & 1) + (g8 >> 1));
                    const float u1 = __shfl_sync(0xffffffffu, e[(i & 2) + 1], 8 * t + 4 * (i & 1) + (g8 >> 1));
                    wg[i] = (g8 & 1) ? u1 : u0;
                }
                mbar_wait(bar_go + 8 * t, 0);
                uint4 pv[4] = {zero4, zero4, zero4, zero4};
                {
                    uint32_t n = 0;
                    while (true) {
                        bool m[4], miss = false;
#pragma unroll
                        for (int i = 0; i < 4; i++) { m[i] = !all_set(pv[i]); miss |= m[i]; }
                        if (!__any_sync(0xffffffffu, miss)) break;
                        if (t < 3 && n) __nanosleep(300);
#pragma unroll
                        for (int i = 0; i < 4; i++) poll128(pv[i], psrc + 256 * t + 32 * i, m[i]);
                        if (++n > SPIN_LIMIT) __trap();
                    }
                }
                const float x = (wg[0] * __uint_as_float(pv[0].x) + wg[1] * __uint_as_float(pv[1].x)) + (wg[2] * __uint_as_float(pv[2].x) + wg[3] * __uint_as_float(pv[3].x));
                const float y = (wg[0] * __uint_as_float(pv[0].y) + wg[1] * __uint_as_float(pv[1].y)) + (wg[2] * __uint_as_float(pv[2].y) + wg[3] * __uint_as_float(pv[3].y));
                const float z = (wg[0] * __uint_as_float(pv[0].z) + wg[1] * __uint_as_float(pv[1].z)) + (wg[2] * __uint_as_float(pv[2].z) + wg[3] * __uint_as_float(pv[3].z));
                const float w = (wg[0] * __uint_as_float(pv[0].w) + wg[1] * __uint_as_float(pv[1].w)) + (wg[2] * __uint_as_float(pv[2].w) + wg[3] * __uint_as_float(pv[3].w));
                float k0 = (up ? z : x) + __shfl_xor_sync(0xffffffffu, up ? x : z, 16);
                float k1 = (up ? w : y) + __shfl_xor_sync(0xffffffffu, up ? y : w, 16);
#pragma unroll
                for (int o = 8; o > 2; o >>= 1) {
                    k0 += __shfl_xor_sync(0xffffffffu, k0, o);
                    k1 += __shfl_xor_sync(0xffffffffu, k1, o);
                }
                if ((lane & 12) == 0) sts32(of_addr + 8 * t, pack_bf16(k0, k1));
                __syncwarp();
                if (lane == 0) mbar_arrive(t < 3 ? bar_ofa : bar_of);
            }
            if (wu == 9) return;
        }
        if (wu == 11 && lane < 4) mbar_expect(bar_wo + 8 * lane, 18432);
        if (wu == 12) {
            if (lane == 0) {
                uint32_t rep = 0, n = 0;
                while (rep < 64u) {
                    const uint32_t cur = lds32v(sb + SM_PROG + 4);
                    if (cur == rep) { __nanosleep(40); if (++n > (SPIN_LIMIT << 2)) __trap(); continue; }
                    uint32_t v;
                    asm volatile("atom.relaxed.gpu.global.add.u32 %0, [%1], %2;" : "=r"(v) : "l"(g_s.cnt + 64), "r"(cur - rep) : "memory");
                    sts32(sb + SM_PROG, v);
                    rep = cur;
                }
            }
            __syncwarp();
        }
        const int u = (wu - 10) * 64 + c;
        if (u >= 144) return;
        const float4* const osrc = g_s.out + (prob * 64 + lane) * 144 + u;
        const bool up = lane >= 16;
        uint32_t* const optr = reinterpret_cast<uint32_t*>(prm.out + prob * 576 + 16 * (u >> 2) + 2 * (u & 3) + (up ? 8 : 0));
        mbar_wait(bar_gd, 0);
        uint4 a = zero4, b = zero4;
        poll2(a, osrc, b, osrc + 32 * 144, 0);
        const float x = __uint_as_float(a.x) + __uint_as_float(b.x), y = __uint_as_float(a.y) + __uint_as_float(b.y);
        const float z = __uint_as_float(a.z) + __uint_as_float(b.z), w = __uint_as_float(a.w) + __uint_as_float(b.w);
        float k0 = (up ? y : x) + __shfl_xor_sync(0xffffffffu, up ? x : y, 16);
        float k1 = (up ? w : z) + __shfl_xor_sync(0xffffffffu, up ? z : w, 16);
#pragma unroll
        for (int o = 8; o > 0; o >>= 1) {
            k0 += __shfl_xor_sync(0xffffffffu, k0, o);
            k1 += __shfl_xor_sync(0xffffffffu, k1, o);
        }
        if ((lane & 15) == 0) *optr = pack_bf16(k0, k1);
        return;
    } else if (wu < 8) {
        {
            uint32_t xb[3][12];
            mbar_wait(bar_x, 0);
#pragma unroll
            for (int b = 0; b < 3; b++)
#pragma unroll
                for (int t = 0; t < 12; t++) xb[b][t] = lds32v(sb + SM_X + ((warp >> 2) * 48 + j4 + b * 96 + 4 * t) * 4);
            float c0[4] = {0.f, 0.f, 0.f, 0.f}, c1[4] = {0.f, 0.f, 0.f, 0.f};
            const uint32_t base = sb + SM_RING + ((warp >> 2) * 96 + (m4 >> 1) * 8 + l8) * 128 + (((2 * (warp & 3) + (m4 & 1)) ^ l8) << 4);
#pragma unroll
            for (int b = 0; b < 3; b++) {
                mbar_wait(bar_full + 16 * b + 8 * (warp >> 2), 0);
#pragma unroll
                for (int t = 0; t < 3; t++) {
                    uint32_t a0[4], a1[4];
                    ldsm4t(a0, base + b * TILE + (2 * t) * 2048);
                    ldsm4t(a1, base + b * TILE + (2 * t + 1) * 2048);
                    mma16816(c0, a0, xb[b][4 * t], xb[b][4 * t + 1]);
                    mma16816(c1, a1, xb[b][4 * t + 2], xb[b][4 * t + 3]);
                }
                __syncwarp();
                if (lane == 0) mbar_arrive(bar_empty + 8 * b);
            }
            if (j4 < 2) sts32(sb + SM_RED + (warp * 16 + g8 + 8 * j4) * 4, __float_as_uint(j4 ? c0[2] + c1[2] : c0[0] + c1[0]));
        }
        bar_consumers();
        if (warp == 0) {
            const float2 va = lds64f(sb + SM_RED + lane * 8), vb = lds64f(sb + SM_RED + 256 + lane * 8);
            uint32_t u = pack_bf16(va.x + vb.x, va.y + vb.y);
            if (u == 0u) u = 0x8000u;
            const int d = 64 * (c & 1) + 2 * lane;
            const int w16 = 2 * (d >> 4) + ((d >> 3) & 1);
            stg32(reinterpret_cast<uint32_t*>(g_s.q) + (bid >> 2) * 128 + (w16 >> 2) * 32 + ((c >> 1) & 1) * 16 + ((d & 7) >> 1) * 4 + (w16 & 3), u);
        }
        {
            uint4 v = zero4, v2 = zero4;
            mbar_wait(bar_full + 8 * 9, 0);
            poll2(v, g_s.q + prob * 512 + tid, v2, g_s.q + prob * 512 + 256 + tid, 300);
            sts128(sb + SM_Q + tid * 16, v);
            sts128(sb + SM_Q + 4096 + tid * 16, v2);
        }
        bar_consumers();
        const uint32_t frag_off = (g8 & 1) * 64 + j4 * 16;
        int s = 3, ph = 0;

        {
            const uint32_t kbase = sb + SM_RING + (2 * warp + (m4 & 1)) * 2048 + l8 * 128 + (((m4 >> 1) ^ l8) << 4);
            const uint32_t sc_addr = sb + SM_SC + (warp * 32 + (j4 & 1) * 16 + (g8 >> 1) * 4 + (g8 & 1) + (j4 >> 1) * 2) * 4;
            uint4 qb[4];
#pragma unroll 1
            for (int i = 0; i < 16; i++) {
                {
#pragma unroll
                    for (int q = 0; q < 4; q++) qb[q] = lds128(sb + SM_Q + i * 512 + q * 128 + frag_off);
                }
                mbar_wait(bar_full + 16 * s + 8 * (warp >> 2), ph);
                float c0[4] = {0.f, 0.f, 0.f, 0.f}, c1[4] = {0.f, 0.f, 0.f, 0.f};
                const uint32_t kb = kbase + s * TILE;
#pragma unroll
                for (int q = 0; q < 4; q++) {
                    uint32_t a0[4], a1[4];
                    ldsm4(a0, (kb ^ (((2 * q) & 3) << 5)) + (q >> 1) * 1024);
                    ldsm4(a1, (kb ^ (((2 * q + 1) & 3) << 5)) + (q >> 1) * 1024);
                    mma16816(c0, a0, qb[q].x, qb[q].y);
                    mma16816(c1, a1, qb[q].z, qb[q].w);
                }
                __syncwarp();
                if (lane == 0) mbar_arrive(bar_empty + 8 * s);
                sts32(sc_addr + i * 1024, __float_as_uint(sel4(c0, j4) + sel4(c1, j4)));
                if (++s == NST) { s = 0; ph ^= 1; }
            }
        }
        mbar_wait(bar_ready, 0);
        bar_consumers();

        {
            constexpr float SCALE = 0.08838834764831845f * 1.4426950408889634f;
            const int hd = warp & 1, st = warp >> 1;
            float4 sv[4];
            float ms[4], sum[4];
#pragma unroll
            for (int t = 0; t < 4; t++) {
                sv[t] = lds128f(sb + SM_SC + ((4 * st + t) * 256 + g8 * 32 + hd * 16 + j4 * 4) * 4);
                ms[t] = fmaxf(fmaxf(sv[t].x, sv[t].y), fmaxf(sv[t].z, sv[t].w));
            }
#pragma unroll
            for (int o = 16; o > 0; o >>= 1)
#pragma unroll
                for (int t = 0; t < 4; t++) ms[t] = fmaxf(ms[t], __shfl_xor_sync(0xffffffffu, ms[t], o));
#pragma unroll
            for (int t = 0; t < 4; t++) {
                ms[t] *= SCALE;
                const float m = ms[t];
                const float p0 = ex2(fmaf(sv[t].x, SCALE, -m)), p1 = ex2(fmaf(sv[t].y, SCALE, -m));
                const float p2 = ex2(fmaf(sv[t].z, SCALE, -m)), p3 = ex2(fmaf(sv[t].w, SCALE, -m));
                sum[t] = (p0 + p1) + (p2 + p3);
                sts64(sb + SM_P + (4 * st + t) * 512 + (g8 >> 1) * 128 + hd * 64 + j4 * 16 + (g8 & 1) * 8, pack_bf16(p0, p1), pack_bf16(p2, p3));
            }
            bar_consumers();
#pragma unroll
            for (int o = 16; o > 0; o >>= 1)
#pragma unroll
                for (int t = 0; t < 4; t++) sum[t] += __shfl_xor_sync(0xffffffffu, sum[t], o);
            if (lane < 4)
                stg64(reinterpret_cast<float2*>(g_s.stat) + ((prob * 2 + hd) * 16 + 4 * st + lane) * 64 + c, nz(sel4(ms, lane)), nz(sel4(sum, lane)));
        }

        {
            const uint32_t vbase = sb + SM_RING + (m4 >> 1) * 2048 + (warp >> 2) * 1024 + l8 * 128 + (((2 * (warp & 3) + (m4 & 1)) ^ l8) << 4);
            float* const dst = reinterpret_cast<float*>(g_s.part) + (prob * 64 + 8 * (j4 & 1) + warp) * 4096 + c * 16 + g8 + 8 * (j4 >> 1);
            const int go_off = 3 + (c >> 4);
            float c0[4] = {0.f, 0.f, 0.f, 0.f}, c1[4] = {0.f, 0.f, 0.f, 0.f};
#pragma unroll 1
            for (int i = 0; i < 16; i++) {
                uint4 pb[4];
#pragma unroll
                for (int q = 0; q < 4; q++) pb[q] = lds128(sb + SM_P + i * 512 + q * 128 + frag_off);
                const uint32_t vb = vbase + s * TILE;
#pragma unroll
                for (int q = 0; q < 4; q++) {
                    uint32_t a0[4], a1[4];
                    if ((q & 1) == 0) mbar_wait(bar_full + 16 * s + 4 * q, ph);
                    ldsm4t(a0, vb + (2 * q) * 4096);
                    ldsm4t(a1, vb + (2 * q + 1) * 4096);
                    mma16816(c0, a0, pb[q].x, pb[q].y);
                    mma16816(c1, a1, pb[q].z, pb[q].w);
                }
                __syncwarp();
                if (lane == 0) mbar_arrive(bar_empty + 8 * s);
                {
                    stg32(dst + (i & 3) * (16 * 4096) + (i >> 2) * 1024, nz(sel4(c0, j4) + sel4(c1, j4)));
#pragma unroll
                    for (int e = 0; e < 4; e++) { c0[e] = 0.f; c1[e] = 0.f; }
                }
                if (tid == 0 && (i == 15 || (i >= go_off && i < go_off + 12 && ((i - go_off) & 3) == 0))) mbar_arrive(bar_go + (i == 15 ? 24 : 2 * (i - go_off)));
                if (++s == NST) { s = 0; ph ^= 1; }
            }
        }
    }

    {
        float acc[2][4][4];
#pragma unroll
        for (int e = 0; e < 32; e++) (&acc[0][0][0])[e] = 0.f;
        const int rho = 9 * ((m4 >> 1) * 8 + l8) + warp;
        uint32_t base[4];
#pragma unroll
        for (int mt = 0; mt < 4; mt++) base[mt] = (sb + SM_RING + rho * 128 + (((m4 & 1) ^ (rho & 7)) << 4)) ^ (mt << 5);
        float* dst = reinterpret_cast<float*>(g_s.out) + bid * 576 + warp * 64 + 16 * j4 + 2 * g8;
        uint32_t js = j4, of_addr = sb + SM_OF + (g8 & 1) * 128 + j4 * 32;
        asm volatile("" : "+r"(base[0]), "+r"(base[1]), "+r"(base[2]), "+r"(base[3]), "+l"(dst), "+r"(js), "+r"(of_addr));
        uint32_t wa[2][4][4];
#define LOAD_W(t) _Pragma("unroll") for (int mt = 0; mt < 4; mt++) ldsm4t(wa[(t) & 1][mt], base[mt] + ((t) ? ((t) - 1) * 18432 : 5 * TILE))
#define MMA_W(t, b0, b1) _Pragma("unroll") for (int mt = 0; mt < 4; mt++) mma16816(acc[(t) & 1][mt], wa[(t) & 1][mt], b0, b1)
        auto pick = [&](int a, int e) {
            float r;
            asm("{\n .reg .pred p, q;\n .reg .f32 u, v;\n .reg .b32 t;\n and.b32 t, %5, 1;\n setp.ne.u32 p, t, 0;\n setp.gt.u32 q, %5, 1;\n"
                " selp.f32 u, %2, %1, p;\n selp.f32 v, %4, %3, p;\n selp.f32 %0, v, u, q;\n}"
                : "=f"(r) : "f"(acc[a][0][e]), "f"(acc[a][1][e]), "f"(acc[a][2][e]), "f"(acc[a][3][e]), "r"(js));
            return r;
        };
        mbar_wait(bar_ofa, 0);
        const uint4 o0 = lds128(of_addr);
        const float2 o1 = lds64f(of_addr + 16);
        mbar_wait(bar_wo, 0);
        LOAD_W(0);
        MMA_W(0, o0.x, o0.y);
        mbar_wait(bar_wo + 8, 0);
        LOAD_W(1);
        MMA_W(1, o0.z, o0.w);
        mbar_wait(bar_wo + 16, 0);
        LOAD_W(2);
        const bool have_w = mbar_test(bar_wo + 24, 0);
        if (have_w) { LOAD_W(3); }
        MMA_W(2, __float_as_uint(o1.x), __float_as_uint(o1.y));
        float2 o2;
        bool have_o = false;
        if (!have_w) {
            uint32_t n = 0;
            while (!mbar_test(bar_wo + 24, 0)) {
                if (mbar_test(bar_of, 0)) {
                    o2 = lds64f(of_addr + 24);
                    have_o = true;
                    mbar_wait(bar_wo + 24, 0);
                    break;
                }
                if (++n > (SPIN_LIMIT << 4)) __trap();
            }
            LOAD_W(3);
        }
        if (!have_o) { mbar_wait(bar_of, 0); o2 = lds64f(of_addr + 24); }
        MMA_W(3, __float_as_uint(o2.x), __float_as_uint(o2.y));
        stg64(dst, nz((pick(0, 0) + pick(0, 1)) + (pick(1, 0) + pick(1, 1))), nz((pick(0, 2) + pick(0, 3)) + (pick(1, 2) + pick(1, 3))));
        if (lane == 0) mbar_arrive(bar_gd);
#undef LOAD_W
#undef MMA_W
    }
}

typedef CUresult (*EncodeFn)(CUtensorMap*, CUtensorMapDataType, cuuint32_t, void*, const cuuint64_t*, const cuuint64_t*,
                             const cuuint32_t*, const cuuint32_t*, CUtensorMapInterleave, CUtensorMapSwizzle,
                             CUtensorMapL2promotion, CUtensorMapFloatOOBfill);

}

extern "C" void kernel_launch(void* const* d_in, const int* in_sizes, int n_in, void* d_out, int out_size) {
    (void)in_sizes; (void)n_in; (void)out_size;
    static EncodeFn enc = nullptr;
    if (!enc) {
        cudaDriverEntryPointQueryResult qr;
        void* fn = nullptr;
        cudaGetDriverEntryPoint("cuTensorMapEncodeTiled", &fn, cudaEnableDefault, &qr);
        enc = (EncodeFn)fn;
        cudaFuncSetAttribute(gqa2_decode_kernel, cudaFuncAttributeMaxDynamicSharedMemorySize, SM_TOTAL);
    }
    Params prm;
    const cuuint32_t es[4] = {1, 1, 1, 1};
    for (int p = 0; p < 2; p++) {
        prm.x[p] = (const __nv_bfloat16*)d_in[5 * p + 0];
        void* ptr[4] = {d_in[5 * p + 3], d_in[5 * p + 1], d_in[5 * p + 2], d_in[5 * p + 4]};
        const cuuint64_t gd[4][4] = {{4096, 576, 1, 1}, {64, 8, 2, 16 * 8192 / 8}, {64, 8, 2, 16 * 8192 / 8}, {64, 4096 * 9, 1, 1}};
        const cuuint64_t gs[4][3] = {{8192, 8192 * 576, 8192 * 576}, {256, 128, 2048}, {256, 128, 2048}, {128, 128 * 4096 * 9, 128 * 4096 * 9}};
        const cuuint32_t bd[4][4] = {{64, 96, 1, 1}, {64, 8, 2, 8}, {64, 8, 2, 8}, {64, 144, 1, 1}};
        for (int i = 0; i < 4; i++)
            enc(&prm.tm[p][i], CU_TENSOR_MAP_DATA_TYPE_BFLOAT16, 4, ptr[i], gd[i], gs[i], bd[i], es,
                CU_TENSOR_MAP_INTERLEAVE_NONE, CU_TENSOR_MAP_SWIZZLE_128B, CU_TENSOR_MAP_L2_PROMOTION_L2_128B,
                CU_TENSOR_MAP_FLOAT_OOB_FILL_NONE);
    }
    prm.out = (__nv_bfloat16*)d_out;
    gqa2_decode_kernel<<<128, NTHREADS, SM_TOTAL>>>(prm);
}
```

```cpp
#include <cuda_runtime.h>
#include <cuda_bf16.h>
#include <cuda.h>
#include <stdint.h>

namespace {

constexpr int TILE = 32768;
constexpr int NST  = 6;
constexpr int DEPTH = 4;
constexpr int NTHREADS = 416;

constexpr int SM_RING = 0;
constexpr int SM_SC   = NST * TILE;
constexpr int SM_P    = SM_SC + 16384;
constexpr int SM_Q    = SM_P;
constexpr int SM_X    = SM_P + 8192;
constexpr int SM_RED  = SM_X + 1152;
constexpr int SM_OF   = SM_RED + 512;
constexpr int SM_PROG = SM_OF + 256;
constexpr int SM_BAR  = SM_PROG + 16;
constexpr int SM_TOTAL = SM_BAR + 320 + 1024;

struct alignas(64) Params {
    CUtensorMap tm[2][4];
    const __nv_bfloat16* x[2];
    __nv_bfloat16* out;
};

struct alignas(4096) Scratch {
    float4 out[128 * 144];
    float4 part[128 * 1024];
    uint4  q[128 * 8];
    float4 stat[128 * 16];
    unsigned int cnt[3 * 32];
};
__device__ Scratch g_s;

constexpr uint32_t SPIN_LIMIT = 1u << 22;

__device__ __forceinline__ void mbar_init(uint32_t a, uint32_t c) {
    asm volatile("mbarrier.init.shared::cta.b64 [%0], %1;" ::"r"(a), "r"(c) : "memory");
}
__device__ __forceinline__ void mbar_expect(uint32_t a, uint32_t b) {
    asm volatile("mbarrier.arrive.expect_tx.shared::cta.b64 _, [%0], %1;" ::"r"(a), "r"(b) : "memory");
}
__device__ __forceinline__ void mbar_arrive(uint32_t a) {
    asm volatile("mbarrier.arrive.shared::cta.b64 _, [%0];" ::"r"(a) : "memory");
}
__device__ __forceinline__ void mbar_wait(uint32_t a, uint32_t ph) {
    uint32_t ok, n = 0;
    do {
        asm volatile("{\n .reg .pred p;\n mbarrier.try_wait.parity.shared::cta.b64 p, [%1], %2;\n selp.u32 %0, 1, 0, p;\n}"
                     : "=r"(ok) : "r"(a), "r"(ph) : "memory");
        if (++n > SPIN_LIMIT) __trap();
    } while (!ok);
}
__device__ __forceinline__ bool mbar_test(uint32_t a, uint32_t ph) {
    uint32_t ok;
    asm volatile("{\n .reg .pred p;\n mbarrier.test_wait.parity.shared::cta.b64 p, [%1], %2;\n selp.u32 %0, 1, 0, p;\n}"
                 : "=r"(ok) : "r"(a), "r"(ph) : "memory");
    return __all_sync(0xffffffffu, ok != 0);
}
__device__ __forceinline__ void tma4d(uint32_t dst, const CUtensorMap* tm, int c0, int c1, int c3, uint32_t mbar, uint64_t pol) {
    asm volatile("cp.async.bulk.tensor.4d.shared::cluster.global.mbarrier::complete_tx::bytes.L2::cache_hint"
                 " [%0], [%1, {%3, %4, %5, %6}], [%2], %7;"
                 ::"r"(dst), "l"(tm), "r"(mbar), "r"(c0), "r"(c1), "r"(0), "r"(c3), "l"(pol) : "memory");
}
__device__ __forceinline__ void ldsm4(uint32_t (&r)[4], uint32_t a) {
    asm volatile("ldmatrix.sync.aligned.m8n8.x4.shared.b16 {%0,%1,%2,%3}, [%4];"
                 : "=r"(r[0]), "=r"(r[1]), "=r"(r[2]), "=r"(r[3]) : "r"(a) : "memory");
}
__device__ __forceinline__ void ldsm4t(uint32_t (&r)[4], uint32_t a) {
    asm volatile("ldmatrix.sync.aligned.m8n8.x4.trans.shared.b16 {%0,%1,%2,%3}, [%4];"
                 : "=r"(r[0]), "=r"(r[1]), "=r"(r[2]), "=r"(r[3]) : "r"(a) : "memory");
}
__device__ __forceinline__ void mma16816(float (&c)[4], const uint32_t (&a)[4], uint32_t b0, uint32_t b1) {
    asm volatile("mma.sync.aligned.m16n8k16.row.col.f32.bf16.bf16.f32 {%0,%1,%2,%3}, {%4,%5,%6,%7}, {%8,%9}, {%0,%1,%2,%3};"
                 : "+f"(c[0]), "+f"(c[1]), "+f"(c[2]), "+f"(c[3])
                 : "r"(a[0]), "r"(a[1]), "r"(a[2]), "r"(a[3]), "r"(b0), "r"(b1));
}
__device__ __forceinline__ uint4 lds128(uint32_t a) {
    uint4 v;
    asm volatile("ld.shared.v4.u32 {%0,%1,%2,%3}, [%4];" : "=r"(v.x), "=r"(v.y), "=r"(v.z), "=r"(v.w) : "r"(a) : "memory");
    return v;
}
__device__ __forceinline__ float4 lds128f(uint32_t a) {
    float4 v;
    asm volatile("ld.shared.v4.f32 {%0,%1,%2,%3}, [%4];" : "=f"(v.x), "=f"(v.y), "=f"(v.z), "=f"(v.w) : "r"(a) : "memory");
    return v;
}
__device__ __forceinline__ float2 lds64f(uint32_t a) {
    float2 v;
    asm volatile("ld.shared.v2.f32 {%0,%1}, [%2];" : "=f"(v.x), "=f"(v.y) : "r"(a) : "memory");
    return v;
}
__device__ __forceinline__ uint32_t lds32v(uint32_t a) {
    uint32_t v;
    asm volatile("ld.volatile.shared.u32 %0, [%1];" : "=r"(v) : "r"(a) : "memory");
    return v;
}
__device__ __forceinline__ void sts128(uint32_t a, uint4 v) {
    asm volatile("st.shared.v4.u32 [%0], {%1,%2,%3,%4};" ::"r"(a), "r"(v.x), "r"(v.y), "r"(v.z), "r"(v.w) : "memory");
}
__device__ __forceinline__ void sts64(uint32_t a, uint32_t x, uint32_t y) {
    asm volatile("st.shared.v2.u32 [%0], {%1,%2};" ::"r"(a), "r"(x), "r"(y) : "memory");
}
__device__ __forceinline__ void sts32(uint32_t a, uint32_t x) {
    asm volatile("st.volatile.shared.u32 [%0], %1;" ::"r"(a), "r"(x) : "memory");
}
__device__ __forceinline__ void poll128(uint4& v, const void* p, bool pred) {
    asm volatile("{\n .reg .pred p;\n setp.ne.u32 p, %5, 0;\n @p ld.relaxed.gpu.global.v4.u32 {%0,%1,%2,%3}, [%4];\n}"
                 : "+r"(v.x), "+r"(v.y), "+r"(v.z), "+r"(v.w) : "l"(p), "r"((uint32_t)pred) : "memory");
}
__device__ __forceinline__ void stg128(void* p, uint4 v) {
    asm volatile("st.relaxed.gpu.global.v4.u32 [%0], {%1,%2,%3,%4};" ::"l"(p), "r"(v.x), "r"(v.y), "r"(v.z), "r"(v.w) : "memory");
}
__device__ __forceinline__ void stg64(void* p, uint32_t x, uint32_t y) {
    asm volatile("st.relaxed.gpu.global.v2.u32 [%0], {%1,%2};" ::"l"(p), "r"(x), "r"(y) : "memory");
}
__device__ __forceinline__ void stg32(void* p, uint32_t x) {
    asm volatile("st.relaxed.gpu.global.u32 [%0], %1;" ::"l"(p), "r"(x) : "memory");
}
__device__ __forceinline__ uint32_t nz(float f) {
    uint32_t u = __float_as_uint(f);
    return u == 0u ? 0x80000000u : u;
}
__device__ __forceinline__ bool all_set(const uint4& v) { return v.x != 0u && v.y != 0u && v.z != 0u && v.w != 0u; }
__device__ __forceinline__ void poll2(uint4& a, const void* pa, uint4& b, const void* pb, int sleep_ns) {
    uint32_t n = 0;
    while (true) {
        const bool ma = !all_set(a), mb = !all_set(b);
        if (!__any_sync(0xffffffffu, ma || mb)) break;
        if (sleep_ns && n) __nanosleep(sleep_ns);
        poll128(a, pa, ma);
        poll128(b, pb, mb);
        if (++n > SPIN_LIMIT) __trap();
    }
}
__device__ __forceinline__ uint32_t pack_bf16(float lo, float hi) {
    uint32_t r;
    asm("cvt.rn.bf16x2.f32 %0, %1, %2;" : "=r"(r) : "f"(hi), "f"(lo));
    return r;
}
__device__ __forceinline__ float ex2(float x) {
    float r;
    asm("ex2.approx.ftz.f32 %0, %1;" : "=f"(r) : "f"(x));
    return r;
}
__device__ __forceinline__ float sel4(const float (&c)[4], int j) {
    float a = (j & 1) ? c[1] : c[0];
    float b = (j & 1) ? c[3] : c[2];
    return (j & 2) ? b : a;
}
__device__ __forceinline__ bool elect_one() {
    uint32_t p;
    asm volatile("{\n .reg .pred p;\n elect.sync _|p, 0xffffffff;\n selp.u32 %0, 1, 0, p;\n}" : "=r"(p));
    return p != 0;
}
__device__ __forceinline__ void bar_consumers() { asm volatile("bar.sync 1, 256;" ::: "memory"); }

__global__ void __launch_bounds__(NTHREADS, 1)
gqa2_decode_kernel(const __grid_constant__ Params prm) {
    extern __shared__ unsigned char smem_raw[];
    const uint32_t sb = ((uint32_t)__cvta_generic_to_shared(smem_raw) + 1023u) & ~1023u;
    const int tid = threadIdx.x, warp = tid >> 5, lane = tid & 31;
    const int bid = blockIdx.x, prob = bid >> 6, c = bid & 63;
    const uint32_t bar_full = sb + SM_BAR, bar_wo = bar_full + 16 * NST, bar_empty = bar_wo + 32;
    const uint32_t bar_ready = bar_empty + 8 * NST, bar_x = bar_ready + 8, bar_of = bar_ready + 16,
                   bar_go = bar_ready + 24, bar_ofa = bar_ready + 56, bar_gd = bar_ready + 64;

    int wu = __shfl_sync(0xffffffffu, warp, 0);
    if (wu == 8) {
        uint64_t pol;
        asm volatile("createpolicy.fractional.L2::evict_first.b64 %0, 1.0;" : "=l"(pol));
        if (elect_one()) {
#pragma unroll
            for (int s = 0; s < 2 * NST; s++) mbar_init(bar_full + 8 * s, 1);
            asm volatile("fence.mbarrier_init.release.cluster;" ::: "memory");
#pragma unroll
            for (int n = 0; n < DEPTH; n++) {
                mbar_expect(bar_full + 8 * n, 12288);
                tma4d(sb + SM_RING + (n >> 1) * TILE + (n & 1) * 12288, &prm.tm[prob][0], c * 64, n * 96, 0, bar_full + 8 * n, pol);
            }
#pragma unroll
            for (int s = 0; s < 4; s++) mbar_init(bar_wo + 8 * s, 1);
#pragma unroll
            for (int s = 0; s < NST; s++) mbar_init(bar_empty + 8 * s, 8);
#pragma unroll
            for (int s = 0; s < 7; s++) mbar_init(bar_ready + 8 * s, s == 2 ? 2 : 1);
            mbar_init(bar_ofa, 6);
            mbar_init(bar_gd, 9);
            asm volatile("fence.mbarrier_init.release.cluster;" ::: "memory");
            mbar_expect(bar_x, 1152);
            asm volatile("cp.async.bulk.shared::cluster.global.mbarrier::complete_tx::bytes [%0], [%1], 1152, [%2];"
                         ::"r"(sb + SM_X), "l"(prm.x[prob]), "r"(bar_x) : "memory");
            sts64(sb + SM_PROG, 0u, 0u);
#pragma unroll
            for (int k = 1; k < 4; k++) asm volatile("prefetch.tensormap [%0];" ::"l"(&prm.tm[prob][k]) : "memory");
        }
        __syncwarp();
        asm volatile("bar.arrive 3, %0;" ::"n"(NTHREADS) : "memory");
        int ib = DEPTH, iph = 0;
        int nw = 0, wb = 0, wph = 0;
#pragma unroll 1
        for (int n = DEPTH; n < 70; n++) {
            const bool kv = n >= 6;
            const int bytes = kv ? TILE / 2 : 12288;
            const uint32_t dst = sb + SM_RING + (ib >> 1) * TILE + (ib & 1) * bytes, bar = bar_full + 8 * ib;
            if (n >= 2 * NST && (n & 1) == 0) mbar_wait(bar_empty + 4 * ib, iph ^ 1);
            if (elect_one()) mbar_expect(bar, bytes);
            while (true) {
                int win = DEPTH;
                if (n >= 14) {
                    const int lag = (int)lds32v(sb + SM_PROG) - ((n - 10) * 128 - 256);
                    win = min(max(DEPTH + (lag >> 7), 2), 8);
                }
                if (n - nw < win) break;
                mbar_wait(bar_full + 8 * wb, wph);
                nw++;
                if (++wb == 2 * NST) { wb = 0; wph ^= 1; }
            }
            if (elect_one()) {
                tma4d(dst, &prm.tm[prob][kv + (n >= 38)], kv ? 0 : c * 64, kv ? 0 : n * 96, kv ? ((n - 6) & 31) * 512 + c * 8 : 0, bar, pol);
                if (n >= 10) sts32(sb + SM_PROG + 4, n - 9);
            }
            if (++ib == 2 * NST) { ib = 0; iph ^= 1; }
        }
#pragma unroll
        for (int k = 0; k < 4; k++) {
            if (k == 0) mbar_wait(bar_empty + 40, 0);
            else if (k < 3) mbar_wait(bar_empty + 8 * (k - 1), 1);
            for (int w = 6; w >= 2; w--) {
                const int m = 70 + k - w;
                mbar_wait(bar_full + 8 * (m < 70 ? m - 60 : m - 58), m < 70 ? 1 : 0);
                const int lag = (int)lds32v(sb + SM_PROG) - ((60 + k) * 128 - 256);
                if (w <= DEPTH + (lag >> 7)) break;
            }
            if (elect_one()) sts32(sb + SM_PROG + 4, 61 + k);
            if (elect_one())
                tma4d(sb + SM_RING + (k ? (k - 1) * 18432 : 5 * TILE), &prm.tm[prob][3], 0, (k * 1024 + c * 16) * 9, 0, bar_wo + 8 * k, pol);
        }
    } else {
        asm volatile("bar.sync 3, %0;" ::"n"(NTHREADS) : "memory");
    }
    asm volatile("" : "+r"(wu));
    const int g8 = lane >> 2, j4 = lane & 3, l8 = lane & 7, m4 = lane >> 3;
    const uint4 zero4 = make_uint4(0u, 0u, 0u, 0u);

    if (wu > 8) {
        if (wu < 11) {
            const int hf = wu - 9;
            float4* const psrc = g_s.part + bid * 1024 + hf * 128 + lane;
#pragma unroll
            for (int i = 0; i < 16; i++) { stg128(psrc + (i >> 2) * 256 + (i & 3) * 32, zero4); __nanosleep(300); }
#pragma unroll
            for (int i = 0; i < 2; i++) stg128(g_s.out + bid * 144 + (2 * hf + i) * 32 + lane, zero4);
            if (lane < 16) stg128(hf == 0 ? g_s.out + bid * 144 + 128 + lane : g_s.stat + bid * 16 + lane, zero4);
            asm volatile("bar.sync 2, 64;" ::: "memory");
            if (tid == 288) {
                unsigned int v, n = 0;
                asm volatile("atom.release.gpu.global.add.u32 %0, [%1], 1;" : "=r"(v) : "l"(g_s.cnt + prob * 32) : "memory");
                const unsigned int target = (v & ~63u) + 64u;
                do {
                    __nanosleep(n ? 1000 : 3000);
                    asm volatile("ld.relaxed.gpu.global.u32 %0, [%1];" : "=r"(v) : "l"(g_s.cnt + prob * 32) : "memory");
                    if (++n > SPIN_LIMIT) __trap();
                } while ((int)(v - target) < 0);
                asm volatile("ld.acquire.gpu.global.u32 %0, [%1];" : "=r"(v) : "l"(g_s.cnt + prob * 32) : "memory");
                mbar_arrive(bar_ready);
            }
            __syncwarp();
            mbar_wait(bar_go, 0);
            float e[4];
            {
                uint4 sa = zero4, sb2 = zero4, sc = zero4, sd = zero4;
                const float4* ssrc = g_s.stat + ((prob * 2 + ((c >> 3) & 1)) * 16 + 4 * m4 + (c >> 4)) * 32 + l8;
                poll128(sc, ssrc + 16 * (1 - hf), true);
                poll128(sd, ssrc + 16 * (1 - hf) + 8, true);
                poll2(sa, ssrc + 16 * hf, sb2, ssrc + 16 * hf + 8, 300);
                poll2(sc, ssrc + 16 * (1 - hf), sd, ssrc + 16 * (1 - hf) + 8, 300);
                if (hf == 0 && lane < 8) stg128(g_s.q + bid * 8 + lane, zero4);
                float M = fmaxf(fmaxf(fmaxf(__uint_as_float(sa.x), __uint_as_float(sa.z)), fmaxf(__uint_as_float(sb2.x), __uint_as_float(sb2.z))),
                                fmaxf(fmaxf(__uint_as_float(sc.x), __uint_as_float(sc.z)), fmaxf(__uint_as_float(sd.x), __uint_as_float(sd.z))));
#pragma unroll
                for (int o = 4; o > 0; o >>= 1) M = fmaxf(M, __shfl_xor_sync(0xffffffffu, M, o));
                e[0] = ex2(__uint_as_float(sa.x) - M); e[1] = ex2(__uint_as_float(sa.z) - M);
                e[2] = ex2(__uint_as_float(sb2.x) - M); e[3] = ex2(__uint_as_float(sb2.z) - M);
                const float La = (e[0] * __uint_as_float(sa.y) + e[1] * __uint_as_float(sa.w)) + (e[2] * __uint_as_float(sb2.y) + e[3] * __uint_as_float(sb2.w));
                const float Lb = (ex2(__uint_as_float(sc.x) - M) * __uint_as_float(sc.y) + ex2(__uint_as_float(sc.z) - M) * __uint_as_float(sc.w)) +
                                 (ex2(__uint_as_float(sd.x) - M) * __uint_as_float(sd.y) + ex2(__uint_as_float(sd.z) - M) * __uint_as_float(sd.w));
                float L = La + Lb;
#pragma unroll
                for (int o = 4; o > 0; o >>= 1) L += __shfl_xor_sync(0xffffffffu, L, o);
                const float inv = 1.0f / L;
#pragma unroll
                for (int i = 0; i < 4; i++) e[i] *= inv;
            }
            const bool up = lane >= 16;
            const int pr = 2 * j4 + (up ? 1 : 0);
            const uint32_t of_addr = sb + SM_OF + hf * 128 + ((pr & 3) * 8 + (pr >> 2)) * 4;
#pragma unroll 1
            for (int t = 0; t < 4; t++) {
                float wg[4];
#pragma unroll
                for (int i = 0; i < 4; i++) {
                    const float u0 = __shfl_sync(0xffffffffu, e[i & 2], 8 * t + 4 * (i & 1) + (g8 >> 1));
                    const float u1 = __shfl_sync(0xffffffffu, e[(i & 2) + 1], 8 * t + 4 * (i & 1) + (g8 >> 1));
                    wg[i] = (g8 & 1) ? u1 : u0;
                }
                mbar_wait(bar_go + 8 * t, 0);
                uint4 pv[4] = {zero4, zero4, zero4, zero4};
                {
                    uint32_t n = 0;
                    while (true) {
                        bool m[4], miss = false;
#pragma unroll
                        for (int i = 0; i < 4; i++) { m[i] = !all_set(pv[i]); miss |= m[i]; }
                        if (!__any_sync(0xffffffffu, miss)) break;
                        if (t < 3 && n) __nanosleep(300);
#pragma unroll
                        for (int i = 0; i < 4; i++) poll128(pv[i], psrc + 256 * t + 32 * i, m[i]);
                        if (++n > SPIN_LIMIT) __trap();
                    }
                }
                const float x = (wg[0] * __uint_as_float(pv[0].x) + wg[1] * __uint_as_float(pv[1].x)) + (wg[2] * __uint_as_float(pv[2].x) + wg[3] * __uint_as_float(pv[3].x));
                const float y = (wg[0] * __uint_as_float(pv[0].y) + wg[1] * __uint_as_float(pv[1].y)) + (wg[2] * __uint_as_float(pv[2].y) + wg[3] * __uint_as_float(pv[3].y));
                const float z = (wg[0] * __uint_as_float(pv[0].z) + wg[1] * __uint_as_float(pv[1].z)) + (wg[2] * __uint_as_float(pv[2].z) + wg[3] * __uint_as_float(pv[3].z));
                const float w = (wg[0] * __uint_as_float(pv[0].w) + wg[1] * __uint_as_float(pv[1].w)) + (wg[2] * __uint_as_float(pv[2].w) + wg[3] * __uint_as_float(pv[3].w));
                float k0 = (up ? z : x) + __shfl_xor_sync(0xffffffffu, up ? x : z, 16);
                float k1 = (up ? w : y) + __shfl_xor_sync(0xffffffffu, up ? y : w, 16);
#pragma unroll
                for (int o = 8; o > 2; o >>= 1) {
                    k0 += __shfl_xor_sync(0xffffffffu, k0, o);
                    k1 += __shfl_xor_sync(0xffffffffu, k1, o);
                }
                if ((lane & 12) == 0) sts32(of_addr + 8 * t, pack_bf16(k0, k1));
                __syncwarp();
                if (lane == 0) mbar_arrive(t < 3 ? bar_ofa : bar_of);
            }
            if (wu == 9) return;
        }
        if (wu == 11 && lane < 4) mbar_expect(bar_wo + 8 * lane, 18432);
        if (wu == 12) {
            if (lane == 0) {
                uint32_t rep = 0, n = 0;
                while (rep < 64u) {
                    const uint32_t cur = lds32v(sb + SM_PROG + 4);
                    if (cur == rep) { __nanosleep(40); if (++n > (SPIN_LIMIT << 2)) __trap(); continue; }
                    uint32_t v;
                    asm volatile("atom.relaxed.gpu.global.add.u32 %0, [%1], %2;" : "=r"(v) : "l"(g_s.cnt + 64), "r"(cur - rep) : "memory");
                    sts32(sb + SM_PROG, v);
                    if (v + (cur - rep) == 128u * 64u) stg32(g_s.cnt + 64, 0u);
                    rep = cur;
                }
            }
            __syncwarp();
        }
        const int u = (wu - 10) * 64 + c;
        if (u >= 144) return;
        const float4* const osrc = g_s.out + (prob * 64 + lane) * 144 + u;
        const bool up = lane >= 16;
        uint32_t* const optr = reinterpret_cast<uint32_t*>(prm.out + prob * 576 + 16 * (u >> 2) + 2 * (u & 3) + (up ? 8 : 0));
        mbar_wait(bar_gd, 0);
        uint4 a = zero4, b = zero4;
        poll2(a, osrc, b, osrc + 32 * 144, 0);
        const float x = __uint_as_float(a.x) + __uint_as_float(b.x), y = __uint_as_float(a.y) + __uint_as_float(b.y);
        const float z = __uint_as_float(a.z) + __uint_as_float(b.z), w = __uint_as_float(a.w) + __uint_as_float(b.w);
        float k0 = (up ? y : x) + __shfl_xor_sync(0xffffffffu, up ? x : y, 16);
        float k1 = (up ? w : z) + __shfl_xor_sync(0xffffffffu, up ? z : w, 16);
#pragma unroll
        for (int o = 8; o > 0; o >>= 1) {
            k0 += __shfl_xor_sync(0xffffffffu, k0, o);
            k1 += __shfl_xor_sync(0xffffffffu, k1, o);
        }
        if ((lane & 15) == 0) *optr = pack_bf16(k0, k1);
        return;
    } else if (wu < 8) {
        {
            uint32_t xb[3][12];
            mbar_wait(bar_x, 0);
#pragma unroll
            for (int b = 0; b < 3; b++)
#pragma unroll
                for (int t = 0; t < 12; t++) xb[b][t] = lds32v(sb + SM_X + ((warp >> 2) * 48 + j4 + b * 96 + 4 * t) * 4);
            float c0[4] = {0.f, 0.f, 0.f, 0.f}, c1[4] = {0.f, 0.f, 0.f, 0.f};
            const uint32_t base = sb + SM_RING + ((warp >> 2) * 96 + (m4 >> 1) * 8 + l8) * 128 + (((2 * (warp & 3) + (m4 & 1)) ^ l8) << 4);
#pragma unroll
            for (int b = 0; b < 3; b++) {
                mbar_wait(bar_full + 16 * b + 8 * (warp >> 2), 0);
#pragma unroll
                for (int t = 0; t < 3; t++) {
                    uint32_t a0[4], a1[4];
                    ldsm4t(a0, base + b * TILE + (2 * t) * 2048);
                    ldsm4t(a1, base + b * TILE + (2 * t + 1) * 2048);
                    mma16816(c0, a0, xb[b][4 * t], xb[b][4 * t + 1]);
                    mma16816(c1, a1, xb[b][4 * t + 2], xb[b][4 * t + 3]);
                }
                __syncwarp();
                if (lane == 0) mbar_arrive(bar_empty + 8 * b);
            }
            if (j4 < 2) sts32(sb + SM_RED + (warp * 16 + g8 + 8 * j4) * 4, __float_as_uint(j4 ? c0[2] + c1[2] : c0[0] + c1[0]));
        }
        bar_consumers();
        if (warp == 0) {
            const float2 va = lds64f(sb + SM_RED + lane * 8), vb = lds64f(sb + SM_RED + 256 + lane * 8);
            uint32_t u = pack_bf16(va.x + vb.x, va.y + vb.y);
            if (u == 0u) u = 0x8000u;
            const int d = 64 * (c & 1) + 2 * lane;
            const int w16 = 2 * (d >> 4) + ((d >> 3) & 1);
            stg32(reinterpret_cast<uint32_t*>(g_s.q) + (bid >> 2) * 128 + (w16 >> 2) * 32 + ((c >> 1) & 1) * 16 + ((d & 7) >> 1) * 4 + (w16 & 3), u);
        }
        {
            uint4 v = zero4, v2 = zero4;
            mbar_wait(bar_full + 8 * 9, 0);
            poll2(v, g_s.q + prob * 512 + tid, v2, g_s.q + prob * 512 + 256 + tid, 300);
            sts128(sb + SM_Q + tid * 16, v);
            sts128(sb + SM_Q + 4096 + tid * 16, v2);
        }
        bar_consumers();
        const uint32_t frag_off = (g8 & 1) * 64 + j4 * 16;
        int s = 3, ph = 0;

        {
            const uint32_t kbase = sb + SM_RING + (2 * warp + (m4 & 1)) * 2048 + l8 * 128 + (((m4 >> 1) ^ l8) << 4);
            const uint32_t sc_addr = sb + SM_SC + (warp * 32 + (j4 & 1) * 16 + (g8 >> 1) * 4 + (g8 & 1) + (j4 >> 1) * 2) * 4;
#pragma unroll 1
            for (int i = 0; i < 16; i++) {
                uint4 qb[4];
#pragma unroll
                for (int q = 0; q < 4; q++) qb[q] = lds128(sb + SM_Q + i * 512 + q * 128 + frag_off);
                mbar_wait(bar_full + 16 * s + 8 * (warp >> 2), ph);
                float c0[4] = {0.f, 0.f, 0.f, 0.f}, c1[4] = {0.f, 0.f, 0.f, 0.f};
                const uint32_t kb = kbase + s * TILE;
#pragma unroll
                for (int q = 0; q < 4; q++) {
                    uint32_t a0[4], a1[4];
                    ldsm4(a0, (kb ^ (((2 * q) & 3) << 5)) + (q >> 1) * 1024);
                    ldsm4(a1, (kb ^ (((2 * q + 1) & 3) << 5)) + (q >> 1) * 1024);
                    mma16816(c0, a0, qb[q].x, qb[q].y);
                    mma16816(c1, a1, qb[q].z, qb[q].w);
                }
                __syncwarp();
                if (lane == 0) mbar_arrive(bar_empty + 8 * s);
                sts32(sc_addr + i * 1024, __float_as_uint(sel4(c0, j4) + sel4(c1, j4)));
                if (++s == NST) { s = 0; ph ^= 1; }
            }
        }
        mbar_wait(bar_ready, 0);
        bar_consumers();

        {
            constexpr float SCALE = 0.08838834764831845f * 1.4426950408889634f;
            const int hd = warp & 1, st = warp >> 1;
            float4 sv[4];
            float ms[4], sum[4];
#pragma unroll
            for (int t = 0; t < 4; t++) {
                sv[t] = lds128f(sb + SM_SC + ((4 * st + t) * 256 + g8 * 32 + hd * 16 + j4 * 4) * 4);
                ms[t] = fmaxf(fmaxf(sv[t].x, sv[t].y), fmaxf(sv[t].z, sv[t].w));
            }
#pragma unroll
            for (int o = 16; o > 0; o >>= 1)
#pragma unroll
                for (int t = 0; t < 4; t++) ms[t] = fmaxf(ms[t], __shfl_xor_sync(0xffffffffu, ms[t], o));
#pragma unroll
            for (int t = 0; t < 4; t++) {
                ms[t] *= SCALE;
                const float m = ms[t];
                const float p0 = ex2(fmaf(sv[t].x, SCALE, -m)), p1 = ex2(fmaf(sv[t].y, SCALE, -m));
                const float p2 = ex2(fmaf(sv[t].z, SCALE, -m)), p3 = ex2(fmaf(sv[t].w, SCALE, -m));
                sum[t] = (p0 + p1) + (p2 + p3);
                sts64(sb + SM_P + (4 * st + t) * 512 + (g8 >> 1) * 128 + hd * 64 + j4 * 16 + (g8 & 1) * 8, pack_bf16(p0, p1), pack_bf16(p2, p3));
            }
            bar_consumers();
#pragma unroll
            for (int o = 16; o > 0; o >>= 1)
#pragma unroll
                for (int t = 0; t < 4; t++) sum[t] += __shfl_xor_sync(0xffffffffu, sum[t], o);
            if (lane < 4)
                stg64(reinterpret_cast<float2*>(g_s.stat) + ((prob * 2 + hd) * 16 + 4 * st + lane) * 64 + c, nz(sel4(ms, lane)), nz(sel4(sum, lane)));
        }

        {
            const uint32_t vbase = sb + SM_RING + (m4 >> 1) * 2048 + (warp >> 2) * 1024 + l8 * 128 + (((2 * (warp & 3) + (m4 & 1)) ^ l8) << 4);
            float* const dst = reinterpret_cast<float*>(g_s.part) + (prob * 64 + 8 * (j4 & 1) + warp) * 4096 + c * 16 + g8 + 8 * (j4 >> 1);
            const int go_off = 3 + (c >> 4);
#pragma unroll 1
            for (int i = 0; i < 16; i++) {
                float c0[4] = {0.f, 0.f, 0.f, 0.f}, c1[4] = {0.f, 0.f, 0.f, 0.f};
                uint4 pb[4];
#pragma unroll
                for (int q = 0; q < 4; q++) pb[q] = lds128(sb + SM_P + i * 512 + q * 128 + frag_off);
                const uint32_t vb = vbase + s * TILE;
#pragma unroll
                for (int q = 0; q < 4; q++) {
                    uint32_t a0[4], a1[4];
                    if ((q & 1) == 0) mbar_wait(bar_full + 16 * s + 4 * q, ph);
                    ldsm4t(a0, vb + (2 * q) * 4096);
                    ldsm4t(a1, vb + (2 * q + 1) * 4096);
                    mma16816(c0, a0, pb[q].x, pb[q].y);
                    mma16816(c1, a1, pb[q].z, pb[q].w);
                }
                __syncwarp();
                if (lane == 0) mbar_arrive(bar_empty + 8 * s);
                stg32(dst + (i & 3) * (16 * 4096) + (i >> 2) * 1024, nz(sel4(c0, j4) + sel4(c1, j4)));
                if (tid == 0 && (i == 15 || (i >= go_off && ((i - go_off) & 3) == 0)))
                    mbar_arrive(bar_go + (i == 15 ? 24 : 2 * (i - go_off)));
                if (++s == NST) { s = 0; ph ^= 1; }
            }
        }
    }

    {
        float acc[2][4][4];
#pragma unroll
        for (int e = 0; e < 32; e++) (&acc[0][0][0])[e] = 0.f;
        const int rho = 9 * ((m4 >> 1) * 8 + l8) + warp;
        uint32_t base[4];
#pragma unroll
        for (int mt = 0; mt < 4; mt++) base[mt] = (sb + SM_RING + rho * 128 + (((m4 & 1) ^ (rho & 7)) << 4)) ^ (mt << 5);
        float* dst = reinterpret_cast<float*>(g_s.out) + bid * 576 + warp * 64 + 16 * j4 + 2 * g8;
        uint32_t js = j4, of_addr = sb + SM_OF + (g8 & 1) * 128 + j4 * 32;
        asm volatile("" : "+r"(base[0]), "+r"(base[1]), "+r"(base[2]), "+r"(base[3]), "+l"(dst), "+r"(js), "+r"(of_addr));
        uint32_t wa[2][4][4];
#define LOAD_W(t) _Pragma("unroll") for (int mt = 0; mt < 4; mt++) ldsm4t(wa[(t) & 1][mt], base[mt] + ((t) ? ((t) - 1) * 18432 : 5 * TILE))
#define MMA_W(t, b0, b1) _Pragma("unroll") for (int mt = 0; mt < 4; mt++) mma16816(acc[(t) & 1][mt], wa[(t) & 1][mt], b0, b1)
        auto pick = [&](int a, int e) {
            float r;
            asm("{\n .reg .pred p, q;\n .reg .f32 u, v;\n .reg .b32 t;\n and.b32 t, %5, 1;\n setp.ne.u32 p, t, 0;\n setp.gt.u32 q, %5, 1;\n"
                " selp.f32 u, %2, %1, p;\n selp.f32 v, %4, %3, p;\n selp.f32 %0, v, u, q;\n}"
                : "=f"(r) : "f"(acc[a][0][e]), "f"(acc[a][1][e]), "f"(acc[a][2][e]), "f"(acc[a][3][e]), "r"(js));
            return r;
        };
        mbar_wait(bar_ofa, 0);
        const uint4 o0 = lds128(of_addr);
        const float2 o1 = lds64f(of_addr + 16);
        mbar_wait(bar_wo, 0);
        LOAD_W(0);
        MMA_W(0, o0.x, o0.y);
        mbar_wait(bar_wo + 8, 0);
        LOAD_W(1);
        MMA_W(1, o0.z, o0.w);
        mbar_wait(bar_wo + 16, 0);
        LOAD_W(2);
        const bool have_w = mbar_test(bar_wo + 24, 0);
        if (have_w) { LOAD_W(3); }
        MMA_W(2, __float_as_uint(o1.x), __float_as_uint(o1.y));
        float2 o2;
        bool have_o = false;
        if (!have_w) {
            uint32_t n = 0;
            while (!mbar_test(bar_wo + 24, 0)) {
                if (mbar_test(bar_of, 0)) {
                    o2 = lds64f(of_addr + 24);
                    have_o = true;
                    mbar_wait(bar_wo + 24, 0);
                    break;
                }
                if (++n > (SPIN_LIMIT << 4)) __trap();
            }
            LOAD_W(3);
        }
        if (!have_o) { mbar_wait(bar_of, 0); o2 = lds64f(of_addr + 24); }
        MMA_W(3, __float_as_uint(o2.x), __float_as_uint(o2.y));
        stg64(dst, nz((pick(0, 0) + pick(0, 1)) + (pick(1, 0) + pick(1, 1))), nz((pick(0, 2) + pick(0, 3)) + (pick(1, 2) + pick(1, 3))));
        if (lane == 0) mbar_arrive(bar_gd);
#undef LOAD_W
#undef MMA_W
    }
}

typedef CUresult (*EncodeFn)(CUtensorMap*, CUtensorMapDataType, cuuint32_t, void*, const cuuint64_t*, const cuuint64_t*,
                             const cuuint32_t*, const cuuint32_t*, CUtensorMapInterleave, CUtensorMapSwizzle,
                             CUtensorMapL2promotion, CUtensorMapFloatOOBfill);

}

extern "C" void kernel_launch(void* const* d_in, const int* in_sizes, int n_in, void* d_out, int out_size) {
    (void)in_sizes; (void)n_in; (void)out_size;
    static EncodeFn enc = nullptr;
    if (!enc) {
        cudaDriverEntryPointQueryResult qr;
        void* fn = nullptr;
        cudaGetDriverEntryPoint("cuTensorMapEncodeTiled", &fn, cudaEnableDefault, &qr);
        enc = (EncodeFn)fn;
        cudaFuncSetAttribute(gqa2_decode_kernel, cudaFuncAttributeMaxDynamicSharedMemorySize, SM_TOTAL);
    }
    Params prm;
    const cuuint32_t es[4] = {1, 1, 1, 1};
    for (int p = 0; p < 2; p++) {
        prm.x[p] = (const __nv_bfloat16*)d_in[5 * p + 0];
        void* ptr[4] = {d_in[5 * p + 3], d_in[5 * p + 1], d_in[5 * p + 2], d_in[5 * p + 4]};
        const cuuint64_t gd[4][4] = {{4096, 576, 1, 1}, {64, 8, 2, 16 * 8192 / 8}, {64, 8, 2, 16 * 8192 / 8}, {64, 4096 * 9, 1, 1}};
        const cuuint64_t gs[4][3] = {{8192, 8192 * 576, 8192 * 576}, {256, 128, 2048}, {256, 128, 2048}, {128, 128 * 4096 * 9, 128 * 4096 * 9}};
        const cuuint32_t bd[4][4] = {{64, 96, 1, 1}, {64, 8, 2, 8}, {64, 8, 2, 8}, {64, 144, 1, 1}};
        for (int i = 0; i < 4; i++)
            enc(&prm.tm[p][i], CU_TENSOR_MAP_DATA_TYPE_BFLOAT16, 4, ptr[i], gd[i], gs[i], bd[i], es,
                CU_TENSOR_MAP_INTERLEAVE_NONE, CU_TENSOR_MAP_SWIZZLE_128B, CU_TENSOR_MAP_L2_PROMOTION_L2_128B,
                CU_TENSOR_MAP_FLOAT_OOB_FILL_NONE);
    }
    prm.out = (__nv_bfloat16*)d_out;
    gqa2_decode_kernel<<<128, NTHREADS, SM_TOTAL>>>(prm);
}
```

```cpp
#include <cuda_runtime.h>
#include <cuda_bf16.h>
#include <cuda.h>
#include <stdint.h>

namespace {

constexpr int TILE = 32768;
constexpr int NST  = 6;
constexpr int DEPTH = 4;
constexpr int NTHREADS = 416;

constexpr int SM_RING = 0;
constexpr int SM_SC   = NST * TILE;
constexpr int SM_P    = SM_SC + 16384;
constexpr int SM_Q    = SM_P;
constexpr int SM_X    = SM_P + 8192;
constexpr int SM_RED  = SM_X + 1152;
constexpr int SM_OF   = SM_RED + 512;
constexpr int SM_PROG = SM_OF + 256;
constexpr int SM_BAR  = SM_PROG + 16;
constexpr int SM_TOTAL = SM_BAR + 320 + 1024;

struct alignas(64) Params {
    CUtensorMap tm[2][4];
    const __nv_bfloat16* x[2];
    __nv_bfloat16* out;
};

struct alignas(4096) Scratch {
    float4 out[128 * 144];
    float4 part[128 * 1024];
    uint4  q[128 * 8];
    float4 stat[128 * 16];
    unsigned int cnt[3 * 32];
};
__device__ Scratch g_s;

constexpr uint32_t SPIN_LIMIT = 1u << 22;

__device__ __forceinline__ void mbar_init(uint32_t a, uint32_t c) {
    asm volatile("mbarrier.init.shared::cta.b64 [%0], %1;" ::"r"(a), "r"(c) : "memory");
}
__device__ __forceinline__ void mbar_expect(uint32_t a, uint32_t b) {
    asm volatile("mbarrier.arrive.expect_tx.shared::cta.b64 _, [%0], %1;" ::"r"(a), "r"(b) : "memory");
}
__device__ __forceinline__ void mbar_arrive(uint32_t a) {
    asm volatile("mbarrier.arrive.shared::cta.b64 _, [%0];" ::"r"(a) : "memory");
}
__device__ __forceinline__ void mbar_wait(uint32_t a, uint32_t ph) {
    uint32_t ok, n = 0;
    do {
        asm volatile("{\n .reg .pred p;\n mbarrier.try_wait.parity.shared::cta.b64 p, [%1], %2;\n selp.u32 %0, 1, 0, p;\n}"
                     : "=r"(ok) : "r"(a), "r"(ph) : "memory");
        if (++n > SPIN_LIMIT) __trap();
    } while (!ok);
}
__device__ __forceinline__ bool mbar_test(uint32_t a, uint32_t ph) {
    uint32_t ok;
    asm volatile("{\n .reg .pred p;\n mbarrier.test_wait.parity.shared::cta.b64 p, [%1], %2;\n selp.u32 %0, 1, 0, p;\n}"
                 : "=r"(ok) : "r"(a), "r"(ph) : "memory");
    return __all_sync(0xffffffffu, ok != 0);
}
__device__ __forceinline__ void tma4d(uint32_t dst, const CUtensorMap* tm, int c0, int c1, int c3, uint32_t mbar, uint64_t pol) {
    asm volatile("cp.async.bulk.tensor.4d.shared::cluster.global.mbarrier::complete_tx::bytes.L2::cache_hint"
                 " [%0], [%1, {%3, %4, %5, %6}], [%2], %7;"
                 ::"r"(dst), "l"(tm), "r"(mbar), "r"(c0), "r"(c1), "r"(0), "r"(c3), "l"(pol) : "memory");
}
__device__ __forceinline__ void ldsm4(uint32_t (&r)[4], uint32_t a) {
    asm volatile("ldmatrix.sync.aligned.m8n8.x4.shared.b16 {%0,%1,%2,%3}, [%4];"
                 : "=r"(r[0]), "=r"(r[1]), "=r"(r[2]), "=r"(r[3]) : "r"(a) : "memory");
}
__device__ __forceinline__ void ldsm4t(uint32_t (&r)[4], uint32_t a) {
    asm volatile("ldmatrix.sync.aligned.m8n8.x4.trans.shared.b16 {%0,%1,%2,%3}, [%4];"
                 : "=r"(r[0]), "=r"(r[1]), "=r"(r[2]), "=r"(r[3]) : "r"(a) : "memory");
}
__device__ __forceinline__ void mma16816(float (&c)[4], const uint32_t (&a)[4], uint32_t b0, uint32_t b1) {
    asm volatile("mma.sync.aligned.m16n8k16.row.col.f32.bf16.bf16.f32 {%0,%1,%2,%3}, {%4,%5,%6,%7}, {%8,%9}, {%0,%1,%2,%3};"
                 : "+f"(c[0]), "+f"(c[1]), "+f"(c[2]), "+f"(c[3])
                 : "r"(a[0]), "r"(a[1]), "r"(a[2]), "r"(a[3]), "r"(b0), "r"(b1));
}
__device__ __forceinline__ uint4 lds128(uint32_t a) {
    uint4 v;
    asm volatile("ld.shared.v4.u32 {%0,%1,%2,%3}, [%4];" : "=r"(v.x), "=r"(v.y), "=r"(v.z), "=r"(v.w) : "r"(a) : "memory");
    return v;
}
__device__ __forceinline__ float4 lds128f(uint32_t a) {
    float4 v;
    asm volatile("ld.shared.v4.f32 {%0,%1,%2,%3}, [%4];" : "=f"(v.x), "=f"(v.y), "=f"(v.z), "=f"(v.w) : "r"(a) : "memory");
    return v;
}
__device__ __forceinline__ float2 lds64f(uint32_t a) {
    float2 v;
    asm volatile("ld.shared.v2.f32 {%0,%1}, [%2];" : "=f"(v.x), "=f"(v.y) : "r"(a) : "memory");
    return v;
}
__device__ __forceinline__ uint32_t lds32v(uint32_t a) {
    uint32_t v;
    asm volatile("ld.volatile.shared.u32 %0, [%1];" : "=r"(v) : "r"(a) : "memory");
    return v;
}
__device__ __forceinline__ void sts128(uint32_t a, uint4 v) {
    asm volatile("st.shared.v4.u32 [%0], {%1,%2,%3,%4};" ::"r"(a), "r"(v.x), "r"(v.y), "r"(v.z), "r"(v.w) : "memory");
}
__device__ __forceinline__ void sts64(uint32_t a, uint32_t x, uint32_t y) {
    asm volatile("st.shared.v2.u32 [%0], {%1,%2};" ::"r"(a), "r"(x), "r"(y) : "memory");
}
__device__ __forceinline__ void sts32(uint32_t a, uint32_t x) {
    asm volatile("st.volatile.shared.u32 [%0], %1;" ::"r"(a), "r"(x) : "memory");
}
__device__ __forceinline__ void poll128(uint4& v, const void* p, bool pred) {
    asm volatile("{\n .reg .pred p;\n setp.ne.u32 p, %5, 0;\n @p ld.relaxed.gpu.global.v4.u32 {%0,%1,%2,%3}, [%4];\n}"
                 : "+r"(v.x), "+r"(v.y), "+r"(v.z), "+r"(v.w) : "l"(p), "r"((uint32_t)pred) : "memory");
}
__device__ __forceinline__ void stg128(void* p, uint4 v) {
    asm volatile("st.relaxed.gpu.global.v4.u32 [%0], {%1,%2,%3,%4};" ::"l"(p), "r"(v.x), "r"(v.y), "r"(v.z), "r"(v.w) : "memory");
}
__device__ __forceinline__ void stg64(void* p, uint32_t x, uint32_t y) {
    asm volatile("st.relaxed.gpu.global.v2.u32 [%0], {%1,%2};" ::"l"(p), "r"(x), "r"(y) : "memory");
}
__device__ __forceinline__ void stg32(void* p, uint32_t x) {
    asm volatile("st.relaxed.gpu.global.u32 [%0], %1;" ::"l"(p), "r"(x) : "memory");
}
__device__ __forceinline__ uint32_t nz(float f) {
    uint32_t u = __float_as_uint(f);
    return u == 0u ? 0x80000000u : u;
}
__device__ __forceinline__ bool all_set(const uint4& v) { return v.x != 0u && v.y != 0u && v.z != 0u && v.w != 0u; }
__device__ __forceinline__ void poll2(uint4& a, const void* pa, uint4& b, const void* pb, int sleep_ns) {
    uint32_t n = 0;
    while (true) {
        const bool ma = !all_set(a), mb = !all_set(b);
        if (!__any_sync(0xffffffffu, ma || mb)) break;
        if (sleep_ns && n) __nanosleep(sleep_ns);
        poll128(a, pa, ma);
        poll128(b, pb, mb);
        if (++n > SPIN_LIMIT) __trap();
    }
}
__device__ __forceinline__ uint32_t pack_bf16(float lo, float hi) {
    uint32_t r;
    asm("cvt.rn.bf16x2.f32 %0, %1, %2;" : "=r"(r) : "f"(hi), "f"(lo));
    return r;
}
__device__ __forceinline__ float ex2(float x) {
    float r;
    asm("ex2.approx.ftz.f32 %0, %1;" : "=f"(r) : "f"(x));
    return r;
}
__device__ __forceinline__ float sel4(const float (&c)[4], int j) {
    float a = (j & 1) ? c[1] : c[0];
    float b = (j & 1) ? c[3] : c[2];
    return (j & 2) ? b : a;
}
__device__ __forceinline__ bool elect_one() {
    uint32_t p;
    asm volatile("{\n .reg .pred p;\n elect.sync _|p, 0xffffffff;\n selp.u32 %0, 1, 0, p;\n}" : "=r"(p));
    return p != 0;
}
__device__ __forceinline__ void bar_consumers() { asm volatile("bar.sync 1, 256;" ::: "memory"); }

__global__ void __launch_bounds__(NTHREADS, 1)
gqa2_decode_kernel(const __grid_constant__ Params prm) {
    extern __shared__ unsigned char smem_raw[];
    const uint32_t sb = ((uint32_t)__cvta_generic_to_shared(smem_raw) + 1023u) & ~1023u;
    const int tid = threadIdx.x, warp = tid >> 5, lane = tid & 31;
    const int bid = blockIdx.x, prob = bid >> 6, c = bid & 63;
    const uint32_t bar_full = sb + SM_BAR, bar_wo = bar_full + 16 * NST, bar_empty = bar_wo + 32;
    const uint32_t bar_ready = bar_empty + 8 * NST, bar_x = bar_ready + 8, bar_of = bar_ready + 16,
                   bar_go = bar_ready + 24, bar_ofa = bar_ready + 56, bar_gd = bar_ready + 64;

    int wu = __shfl_sync(0xffffffffu, warp, 0);
    if (wu == 8) {
        uint64_t pol;
        asm volatile("createpolicy.fractional.L2::evict_first.b64 %0, 1.0;" : "=l"(pol));
        if (elect_one()) {
#pragma unroll
            for (int s = 0; s < 2 * NST; s++) mbar_init(bar_full + 8 * s, 1);
            asm volatile("fence.mbarrier_init.release.cluster;" ::: "memory");
#pragma unroll
            for (int n = 0; n < DEPTH; n++) {
                mbar_expect(bar_full + 8 * n, 12288);
                tma4d(sb + SM_RING + (n >> 1) * TILE + (n & 1) * 12288, &prm.tm[prob][0], c * 64, n * 96, 0, bar_full + 8 * n, pol);
            }
#pragma unroll
            for (int s = 0; s < 4; s++) mbar_init(bar_wo + 8 * s, 1);
#pragma unroll
            for (int s = 0; s < NST; s++) mbar_init(bar_empty + 8 * s, 8);
#pragma unroll
            for (int s = 0; s < 7; s++) mbar_init(bar_ready + 8 * s, s == 2 ? 2 : 1);
            mbar_init(bar_ofa, 6);
            mbar_init(bar_gd, 9);
            asm volatile("fence.mbarrier_init.release.cluster;" ::: "memory");
            mbar_expect(bar_x, 1152);
            asm volatile("cp.async.bulk.shared::cluster.global.mbarrier::complete_tx::bytes [%0], [%1], 1152, [%2];"
                         ::"r"(sb + SM_X), "l"(prm.x[prob]), "r"(bar_x) : "memory");
            sts64(sb + SM_PROG, 0u, 0u);
#pragma unroll
            for (int k = 1; k < 4; k++) asm volatile("prefetch.tensormap [%0];" ::"l"(&prm.tm[prob][k]) : "memory");
        }
        __syncwarp();
        asm volatile("bar.arrive 3, %0;" ::"n"(NTHREADS) : "memory");
        int ib = DEPTH, iph = 0;
        int nw = 0, wb = 0, wph = 0;
#pragma unroll 1
        for (int n = DEPTH; n < 70; n++) {
            const bool kv = n >= 6;
            const int bytes = kv ? TILE / 2 : 12288;
            const uint32_t dst = sb + SM_RING + (ib >> 1) * TILE + (ib & 1) * bytes, bar = bar_full + 8 * ib;
            if (n >= 2 * NST && (n & 1) == 0) mbar_wait(bar_empty + 4 * ib, iph ^ 1);
            if (elect_one()) mbar_expect(bar, bytes);
            while (true) {
                int win = DEPTH;
                if (n >= 14) {
                    const int lag = (int)lds32v(sb + SM_PROG) - ((n - 10) * 128 - 256);
                    win = min(max(DEPTH + (lag >> 7), 2), 8);
                }
                if (n - nw < win) break;
                mbar_wait(bar_full + 8 * wb, wph);
                nw++;
                if (++wb == 2 * NST) { wb = 0; wph ^= 1; }
            }
            if (elect_one()) {
                tma4d(dst, &prm.tm[prob][kv + (n >= 38)], kv ? 0 : c * 64, kv ? 0 : n * 96, kv ? ((n - 6) & 31) * 512 + c * 8 : 0, bar, pol);
                if (n >= 10) sts32(sb + SM_PROG + 4, n - 9);
            }
            if (++ib == 2 * NST) { ib = 0; iph ^= 1; }
        }
#pragma unroll
        for (int k = 0; k < 4; k++) {
            if (k == 0) mbar_wait(bar_empty + 40, 0);
            else if (k < 3) mbar_wait(bar_empty + 8 * (k - 1), 1);
            for (int w = 6; w >= 2; w--) {
                const int m = 70 + k - w;
                mbar_wait(bar_full + 8 * (m < 70 ? m - 60 : m - 58), m < 70 ? 1 : 0);
                const int lag = (int)lds32v(sb + SM_PROG) - ((60 + k) * 128 - 256);
                if (w <= DEPTH + (lag >> 7)) break;
            }
            if (elect_one()) sts32(sb + SM_PROG + 4, 61 + k);
            if (elect_one())
                tma4d(sb + SM_RING + (k ? (k - 1) * 18432 : 5 * TILE), &prm.tm[prob][3], 0, (k * 1024 + c * 16) * 9, 0, bar_wo + 8 * k, pol);
        }
    } else {
        asm volatile("bar.sync 3, %0;" ::"n"(NTHREADS) : "memory");
    }
    asm volatile("" : "+r"(wu));
    const int g8 = lane >> 2, j4 = lane & 3, l8 = lane & 7, m4 = lane >> 3;
    const uint4 zero4 = make_uint4(0u, 0u, 0u, 0u);

    if (wu > 8) {
        if (wu < 11) {
            const int hf = wu - 9;
            float4* const psrc = g_s.part + bid * 1024 + hf * 128 + lane;
#pragma unroll
            for (int i = 0; i < 16; i++) { stg128(psrc + (i >> 2) * 256 + (i & 3) * 32, zero4); __nanosleep(300); }
#pragma unroll
            for (int i = 0; i < 2; i++) stg128(g_s.out + bid * 144 + (2 * hf + i) * 32 + lane, zero4);
            if (lane < 16) stg128(hf == 0 ? g_s.out + bid * 144 + 128 + lane : g_s.stat + bid * 16 + lane, zero4);
            asm volatile("bar.sync 2, 64;" ::: "memory");
            if (tid == 288) {
                unsigned int v, n = 0;
                asm volatile("atom.release.gpu.global.add.u32 %0, [%1], 1;" : "=r"(v) : "l"(g_s.cnt + prob * 32) : "memory");
                const unsigned int target = (v & ~63u) + 64u;
                do {
                    __nanosleep(n ? 1000 : 3000);
                    asm volatile("ld.relaxed.gpu.global.u32 %0, [%1];" : "=r"(v) : "l"(g_s.cnt + prob * 32) : "memory");
                    if (++n > SPIN_LIMIT) __trap();
                } while ((int)(v - target) < 0);
                asm volatile("ld.acquire.gpu.global.u32 %0, [%1];" : "=r"(v) : "l"(g_s.cnt + prob * 32) : "memory");
                mbar_arrive(bar_ready);
            }
            __syncwarp();
            mbar_wait(bar_go, 0);
            float e[4];
            {
                uint4 sa = zero4, sb2 = zero4, sc = zero4, sd = zero4;
                const float4* ssrc = g_s.stat + ((prob * 2 + ((c >> 3) & 1)) * 16 + 4 * m4 + (c >> 4)) * 32 + l8;
                poll128(sc, ssrc + 16 * (1 - hf), true);
                poll128(sd, ssrc + 16 * (1 - hf) + 8, true);
                poll2(sa, ssrc + 16 * hf, sb2, ssrc + 16 * hf + 8, 300);
                poll2(sc, ssrc + 16 * (1 - hf), sd, ssrc + 16 * (1 - hf) + 8, 300);
                if (hf == 0 && lane < 8) stg128(g_s.q + bid * 8 + lane, zero4);
                float M = fmaxf(fmaxf(fmaxf(__uint_as_float(sa.x), __uint_as_float(sa.z)), fmaxf(__uint_as_float(sb2.x), __uint_as_float(sb2.z))),
                                fmaxf(fmaxf(__uint_as_float(sc.x), __uint_as_float(sc.z)), fmaxf(__uint_as_float(sd.x), __uint_as_float(sd.z))));
#pragma unroll
                for (int o = 4; o > 0; o >>= 1) M = fmaxf(M, __shfl_xor_sync(0xffffffffu, M, o));
                e[0] = ex2(__uint_as_float(sa.x) - M); e[1] = ex2(__uint_as_float(sa.z) - M);
                e[2] = ex2(__uint_as_float(sb2.x) - M); e[3] = ex2(__uint_as_float(sb2.z) - M);
                const float La = (e[0] * __uint_as_float(sa.y) + e[1] * __uint_as_float(sa.w)) + (e[2] * __uint_as_float(sb2.y) + e[3] * __uint_as_float(sb2.w));
                const float Lb = (ex2(__uint_as_float(sc.x) - M) * __uint_as_float(sc.y) + ex2(__uint_as_float(sc.z) - M) * __uint_as_float(sc.w)) +
                                 (ex2(__uint_as_float(sd.x) - M) * __uint_as_float(sd.y) + ex2(__uint_as_float(sd.z) - M) * __uint_as_float(sd.w));
                float L = La + Lb;
#pragma unroll
                for (int o = 4; o > 0; o >>= 1) L += __shfl_xor_sync(0xffffffffu, L, o);
                const float inv = 1.0f / L;
#pragma unroll
                for (int i = 0; i < 4; i++) e[i] *= inv;
            }
            const bool up = lane >= 16;
            const int pr = 2 * j4 + (up ? 1 : 0);
            const uint32_t of_addr = sb + SM_OF + hf * 128 + ((pr & 3) * 8 + (pr >> 2)) * 4;
#pragma unroll 1
            for (int t = 0; t < 4; t++) {
                float wg[4];
#pragma unroll
                for (int i = 0; i < 4; i++) {
                    const float u0 = __shfl_sync(0xffffffffu, e[i & 2], 8 * t + 4 * (i & 1) + (g8 >> 1));
                    const float u1 = __shfl_sync(0xffffffffu, e[(i & 2) + 1], 8 * t + 4 * (i & 1) + (g8 >> 1));
                    wg[i] = (g8 & 1) ? u1 : u0;
                }
                mbar_wait(bar_go + 8 * t, 0);
                uint4 pv[4] = {zero4, zero4, zero4, zero4};
                {
                    uint32_t n = 0;
                    while (true) {
                        bool m[4], miss = false;
#pragma unroll
                        for (int i = 0; i < 4; i++) { m[i] = !all_set(pv[i]); miss |= m[i]; }
                        if (!__any_sync(0xffffffffu, miss)) break;
                        if (t < 3 && n) __nanosleep(300);
#pragma unroll
                        for (int i = 0; i < 4; i++) poll128(pv[i], psrc + 256 * t + 32 * i, m[i]);
                        if (++n > SPIN_LIMIT) __trap();
                    }
                }
                const float x = (wg[0] * __uint_as_float(pv[0].x) + wg[1] * __uint_as_float(pv[1].x)) + (wg[2] * __uint_as_float(pv[2].x) + wg[3] * __uint_as_float(pv[3].x));
                const float y = (wg[0] * __uint_as_float(pv[0].y) + wg[1] * __uint_as_float(pv[1].y)) + (wg[2] * __uint_as_float(pv[2].y) + wg[3] * __uint_as_float(pv[3].y));
                const float z = (wg[0] * __uint_as_float(pv[0].z) + wg[1] * __uint_as_float(pv[1].z)) + (wg[2] * __uint_as_float(pv[2].z) + wg[3] * __uint_as_float(pv[3].z));
                const float w = (wg[0] * __uint_as_float(pv[0].w) + wg[1] * __uint_as_float(pv[1].w)) + (wg[2] * __uint_as_float(pv[2].w) + wg[3] * __uint_as_float(pv[3].w));
                float k0 = (up ? z : x) + __shfl_xor_sync(0xffffffffu, up ? x : z, 16);
                float k1 = (up ? w : y) + __shfl_xor_sync(0xffffffffu, up ? y : w, 16);
#pragma unroll
                for (int o = 8; o > 2; o >>= 1) {
                    k0 += __shfl_xor_sync(0xffffffffu, k0, o);
                    k1 += __shfl_xor_sync(0xffffffffu, k1, o);
                }
                if ((lane & 12) == 0) sts32(of_addr + 8 * t, pack_bf16(k0, k1));
                __syncwarp();
                if (lane == 0) mbar_arrive(t < 3 ? bar_ofa : bar_of);
            }
            if (wu == 9) return;
        }
        if (wu == 11 && lane < 4) mbar_expect(bar_wo + 8 * lane, 18432);
        if (wu == 12) {
            if (lane == 0) {
                uint32_t rep = 0, n = 0;
                while (rep < 64u) {
                    const uint32_t cur = lds32v(sb + SM_PROG + 4);
                    if (cur == rep) { __nanosleep(40); if (++n > (SPIN_LIMIT << 2)) __trap(); continue; }
                    uint32_t v;
                    asm volatile("atom.relaxed.gpu.global.add.u32 %0, [%1], %2;" : "=r"(v) : "l"(g_s.cnt + 64), "r"(cur - rep) : "memory");
                    sts32(sb + SM_PROG, v);
                    if (v + (cur - rep) == 128u * 64u) stg32(g_s.cnt + 64, 0u);
                    rep = cur;
                }
            }
            __syncwarp();
        }
        const int u = (wu - 10) * 64 + c;
        if (u >= 144) return;
        const float4* const osrc = g_s.out + (prob * 64 + lane) * 144 + u;
        const bool up = lane >= 16;
        uint32_t* const optr = reinterpret_cast<uint32_t*>(prm.out + prob * 576 + 16 * (u >> 2) + 2 * (u & 3) + (up ? 8 : 0));
        mbar_wait(bar_gd, 0);
        uint4 a = zero4, b = zero4;
        poll128(a, osrc, true);
        poll128(b, osrc + 32 * 144, true);
        for (uint32_t n = 0; n <= SPIN_LIMIT; n++) {
            const float x = __uint_as_float(a.x) + __uint_as_float(b.x), y = __uint_as_float(a.y) + __uint_as_float(b.y);
            const float z = __uint_as_float(a.z) + __uint_as_float(b.z), w = __uint_as_float(a.w) + __uint_as_float(b.w);
            float k0 = (up ? y : x) + __shfl_xor_sync(0xffffffffu, up ? x : y, 16);
            float k1 = (up ? w : z) + __shfl_xor_sync(0xffffffffu, up ? z : w, 16);
            const bool ma = !all_set(a), mb = !all_set(b);
            poll128(a, osrc, ma);
            poll128(b, osrc + 32 * 144, mb);
            const bool miss = __any_sync(0xffffffffu, ma || mb);
#pragma unroll
            for (int o = 8; o > 0; o >>= 1) {
                k0 += __shfl_xor_sync(0xffffffffu, k0, o);
                k1 += __shfl_xor_sync(0xffffffffu, k1, o);
            }
            if (!miss) {
                if ((lane & 15) == 0) *optr = pack_bf16(k0, k1);
                return;
            }
        }
        __trap();
    } else if (wu < 8) {
        {
            uint32_t xb[3][12];
            mbar_wait(bar_x, 0);
#pragma unroll
            for (int b = 0; b < 3; b++)
#pragma unroll
                for (int t = 0; t < 12; t++) xb[b][t] = lds32v(sb + SM_X + ((warp >> 2) * 48 + j4 + b * 96 + 4 * t) * 4);
            float c0[4] = {0.f, 0.f, 0.f, 0.f}, c1[4] = {0.f, 0.f, 0.f, 0.f};
            const uint32_t base = sb + SM_RING + ((warp >> 2) * 96 + (m4 >> 1) * 8 + l8) * 128 + (((2 * (warp & 3) + (m4 & 1)) ^ l8) << 4);
#pragma unroll
            for (int b = 0; b < 3; b++) {
                mbar_wait(bar_full + 16 * b + 8 * (warp >> 2), 0);
#pragma unroll
                for (int t = 0; t < 3; t++) {
                    uint32_t a0[4], a1[4];
                    ldsm4t(a0, base + b * TILE + (2 * t) * 2048);
                    ldsm4t(a1, base + b * TILE + (2 * t + 1) * 2048);
                    mma16816(c0, a0, xb[b][4 * t], xb[b][4 * t + 1]);
                    mma16816(c1, a1, xb[b][4 * t + 2], xb[b][4 * t + 3]);
                }
                __syncwarp();
                if (lane == 0) mbar_arrive(bar_empty + 8 * b);
            }
            if (j4 < 2) sts32(sb + SM_RED + (warp * 16 + g8 + 8 * j4) * 4, __float_as_uint(j4 ? c0[2] + c1[2] : c0[0] + c1[0]));
        }
        bar_consumers();
        if (warp == 0) {
            const float2 va = lds64f(sb + SM_RED + lane * 8), vb = lds64f(sb + SM_RED + 256 + lane * 8);
            uint32_t u = pack_bf16(va.x + vb.x, va.y + vb.y);
            if (u == 0u) u = 0x8000u;
            const int d = 64 * (c & 1) + 2 * lane;
            const int w16 = 2 * (d >> 4) + ((d >> 3) & 1);
            stg32(reinterpret_cast<uint32_t*>(g_s.q) + (bid >> 2) * 128 + (w16 >> 2) * 32 + ((c >> 1) & 1) * 16 + ((d & 7) >> 1) * 4 + (w16 & 3), u);
        }
        {
            uint4 v = zero4, v2 = zero4;
            mbar_wait(bar_full + 8 * 9, 0);
            poll2(v, g_s.q + prob * 512 + tid, v2, g_s.q + prob * 512 + 256 + tid, 300);
            sts128(sb + SM_Q + tid * 16, v);
            sts128(sb + SM_Q + 4096 + tid * 16, v2);
        }
        bar_consumers();
        const uint32_t frag_off = (g8 & 1) * 64 + j4 * 16;
        int s = 3, ph = 0;

        {
            const uint32_t kbase = sb + SM_RING + (2 * warp + (m4 & 1)) * 2048 + l8 * 128 + (((m4 >> 1) ^ l8) << 4);
            const uint32_t sc_addr = sb + SM_SC + (warp * 32 + (j4 & 1) * 16 + (g8 >> 1) * 4 + (g8 & 1) + (j4 >> 1) * 2) * 4;
#pragma unroll 1
            for (int i = 0; i < 16; i++) {
                uint4 qb[4];
#pragma unroll
                for (int q = 0; q < 4; q++) qb[q] = lds128(sb + SM_Q + i * 512 + q * 128 + frag_off);
                mbar_wait(bar_full + 16 * s + 8 * (warp >> 2), ph);
                float c0[4] = {0.f, 0.f, 0.f, 0.f}, c1[4] = {0.f, 0.f, 0.f, 0.f};
                const uint32_t kb = kbase + s * TILE;
#pragma unroll
                for (int q = 0; q < 4; q++) {
                    uint32_t a0[4], a1[4];
                    ldsm4(a0, (kb ^ (((2 * q) & 3) << 5)) + (q >> 1) * 1024);
                    ldsm4(a1, (kb ^ (((2 * q + 1) & 3) << 5)) + (q >> 1) * 1024);
                    mma16816(c0, a0, qb[q].x, qb[q].y);
                    mma16816(c1, a1, qb[q].z, qb[q].w);
                }
                __syncwarp();
                if (lane == 0) mbar_arrive(bar_empty + 8 * s);
                sts32(sc_addr + i * 1024, __float_as_uint(sel4(c0, j4) + sel4(c1, j4)));
                if (++s == NST) { s = 0; ph ^= 1; }
            }
        }
        mbar_wait(bar_ready, 0);
        bar_consumers();

        {
            constexpr float SCALE = 0.08838834764831845f * 1.4426950408889634f;
            const int hd = warp & 1, st = warp >> 1;
            float4 sv[4];
            float ms[4], sum[4];
#pragma unroll
            for (int t = 0; t < 4; t++) {
                sv[t] = lds128f(sb + SM_SC + ((4 * st + t) * 256 + g8 * 32 + hd * 16 + j4 * 4) * 4);
                ms[t] = fmaxf(fmaxf(sv[t].x, sv[t].y), fmaxf(sv[t].z, sv[t].w));
            }
#pragma unroll
            for (int o = 16; o > 0; o >>= 1)
#pragma unroll
                for (int t = 0; t < 4; t++) ms[t] = fmaxf(ms[t], __shfl_xor_sync(0xffffffffu, ms[t], o));
#pragma unroll
            for (int t = 0; t < 4; t++) {
                ms[t] *= SCALE;
                const float m = ms[t];
                const float p0 = ex2(fmaf(sv[t].x, SCALE, -m)), p1 = ex2(fmaf(sv[t].y, SCALE, -m));
                const float p2 = ex2(fmaf(sv[t].z, SCALE, -m)), p3 = ex2(fmaf(sv[t].w, SCALE, -m));
                sum[t] = (p0 + p1) + (p2 + p3);
                sts64(sb + SM_P + (4 * st + t) * 512 + (g8 >> 1) * 128 + hd * 64 + j4 * 16 + (g8 & 1) * 8, pack_bf16(p0, p1), pack_bf16(p2, p3));
            }
            bar_consumers();
#pragma unroll
            for (int o = 16; o > 0; o >>= 1)
#pragma unroll
                for (int t = 0; t < 4; t++) sum[t] += __shfl_xor_sync(0xffffffffu, sum[t], o);
            if (lane < 4)
                stg64(reinterpret_cast<float2*>(g_s.stat) + ((prob * 2 + hd) * 16 + 4 * st + lane) * 64 + c, nz(sel4(ms, lane)), nz(sel4(sum, lane)));
        }

        {
            const uint32_t vbase = sb + SM_RING + (m4 >> 1) * 2048 + (warp >> 2) * 1024 + l8 * 128 + (((2 * (warp & 3) + (m4 & 1)) ^ l8) << 4);
            float* const dst = reinterpret_cast<float*>(g_s.part) + (prob * 64 + 8 * (j4 & 1) + warp) * 4096 + c * 16 + g8 + 8 * (j4 >> 1);
            const int go_off = 3 + (c >> 4);
#pragma unroll 1
            for (int i = 0; i < 16; i++) {
                float c0[4] = {0.f, 0.f, 0.f, 0.f}, c1[4] = {0.f, 0.f, 0.f, 0.f};
                uint4 pb[4];
#pragma unroll
                for (int q = 0; q < 4; q++) pb[q] = lds128(sb + SM_P + i * 512 + q * 128 + frag_off);
                const uint32_t vb = vbase + s * TILE;
#pragma unroll
                for (int q = 0; q < 4; q++) {
                    uint32_t a0[4], a1[4];
                    if ((q & 1) == 0) mbar_wait(bar_full + 16 * s + 4 * q, ph);
                    ldsm4t(a0, vb + (2 * q) * 4096);
                    ldsm4t(a1, vb + (2 * q + 1) * 4096);
                    mma16816(c0, a0, pb[q].x, pb[q].y);
                    mma16816(c1, a1, pb[q].z, pb[q].w);
                }
                __syncwarp();
                if (lane == 0) mbar_arrive(bar_empty + 8 * s);
                stg32(dst + (i & 3) * (16 * 4096) + (i >> 2) * 1024, nz(sel4(c0, j4) + sel4(c1, j4)));
                if (tid == 0 && (i == 15 || (i >= go_off && ((i - go_off) & 3) == 0)))
                    mbar_arrive(bar_go + (i == 15 ? 24 : 2 * (i - go_off)));
                if (++s == NST) { s = 0; ph ^= 1; }
            }
        }
    }

    {
        float acc[2][4][4];
#pragma unroll
        for (int e = 0; e < 32; e++) (&acc[0][0][0])[e] = 0.f;
        const int rho = 9 * ((m4 >> 1) * 8 + l8) + warp;
        uint32_t base[4];
#pragma unroll
        for (int mt = 0; mt < 4; mt++) base[mt] = (sb + SM_RING + rho * 128 + (((m4 & 1) ^ (rho & 7)) << 4)) ^ (mt << 5);
        float* dst = reinterpret_cast<float*>(g_s.out) + bid * 576 + warp * 64 + 16 * j4 + 2 * g8;
        uint32_t js = j4, of_addr = sb + SM_OF + (g8 & 1) * 128 + j4 * 32;
        asm volatile("" : "+r"(base[0]), "+r"(base[1]), "+r"(base[2]), "+r"(base[3]), "+l"(dst), "+r"(js), "+r"(of_addr));
        uint32_t wa[2][4][4];
#define LOAD_W(t) _Pragma("unroll") for (int mt = 0; mt < 4; mt++) ldsm4t(wa[(t) & 1][mt], base[mt] + ((t) ? ((t) - 1) * 18432 : 5 * TILE))
#define MMA_W(t, b0, b1) _Pragma("unroll") for (int mt = 0; mt < 4; mt++) mma16816(acc[(t) & 1][mt], wa[(t) & 1][mt], b0, b1)
        auto pick = [&](int a, int e) {
            float r;
            asm("{\n .reg .pred p, q;\n .reg .f32 u, v;\n .reg .b32 t;\n and.b32 t, %5, 1;\n setp.ne.u32 p, t, 0;\n setp.gt.u32 q, %5, 1;\n"
                " selp.f32 u, %2, %1, p;\n selp.f32 v, %4, %3, p;\n selp.f32 %0, v, u, q;\n}"
                : "=f"(r) : "f"(acc[a][0][e]), "f"(acc[a][1][e]), "f"(acc[a][2][e]), "f"(acc[a][3][e]), "r"(js));
            return r;
        };
        mbar_wait(bar_ofa, 0);
        const uint4 o0 = lds128(of_addr);
        const float2 o1 = lds64f(of_addr + 16);
        mbar_wait(bar_wo, 0);
        LOAD_W(0);
        MMA_W(0, o0.x, o0.y);
        mbar_wait(bar_wo + 8, 0);
        LOAD_W(1);
        MMA_W(1, o0.z, o0.w);
        mbar_wait(bar_wo + 16, 0);
        LOAD_W(2);
        const bool have_w = mbar_test(bar_wo + 24, 0);
        if (have_w) { LOAD_W(3); }
        MMA_W(2, __float_as_uint(o1.x), __float_as_uint(o1.y));
        float2 o2;
        bool have_o = false;
        if (!have_w) {
            uint32_t n = 0;
            while (!mbar_test(bar_wo + 24, 0)) {
                if (mbar_test(bar_of, 0)) {
                    o2 = lds64f(of_addr + 24);
                    have_o = true;
                    mbar_wait(bar_wo + 24, 0);
                    break;
                }
                if (++n > (SPIN_LIMIT << 4)) __trap();
            }
            LOAD_W(3);
        }
        if (!have_o) { mbar_wait(bar_of, 0); o2 = lds64f(of_addr + 24); }
        MMA_W(3, __float_as_uint(o2.x), __float_as_uint(o2.y));
        stg64(dst, nz((pick(0, 0) + pick(0, 1)) + (pick(1, 0) + pick(1, 1))), nz((pick(0, 2) + pick(0, 3)) + (pick(1, 2) + pick(1, 3))));
        if (lane == 0) mbar_arrive(bar_gd);
#undef LOAD_W
#undef MMA_W
    }
}

typedef CUresult (*EncodeFn)(CUtensorMap*, CUtensorMapDataType, cuuint32_t, void*, const cuuint64_t*, const cuuint64_t*,
                             const cuuint32_t*, const cuuint32_t*, CUtensorMapInterleave, CUtensorMapSwizzle,
                             CUtensorMapL2promotion, CUtensorMapFloatOOBfill);

}

extern "C" void kernel_launch(void* const* d_in, const int* in_sizes, int n_in, void* d_out, int out_size) {
    (void)in_sizes; (void)n_in; (void)out_size;
    static EncodeFn enc = nullptr;
    if (!enc) {
        cudaDriverEntryPointQueryResult qr;
        void* fn = nullptr;
        cudaGetDriverEntryPoint("cuTensorMapEncodeTiled", &fn, cudaEnableDefault, &qr);
        enc = (EncodeFn)fn;
        cudaFuncSetAttribute(gqa2_decode_kernel, cudaFuncAttributeMaxDynamicSharedMemorySize, SM_TOTAL);
    }
    Params prm;
    const cuuint32_t es[4] = {1, 1, 1, 1};
    for (int p = 0; p < 2; p++) {
        prm.x[p] = (const __nv_bfloat16*)d_in[5 * p + 0];
        void* ptr[4] = {d_in[5 * p + 3], d_in[5 * p + 1], d_in[5 * p + 2], d_in[5 * p + 4]};
        const cuuint64_t gd[4][4] = {{4096, 576, 1, 1}, {64, 8, 2, 16 * 8192 / 8}, {64, 8, 2, 16 * 8192 / 8}, {64, 4096 * 9, 1, 1}};
        const cuuint64_t gs[4][3] = {{8192, 8192 * 576, 8192 * 576}, {256, 128, 2048}, {256, 128, 2048}, {128, 128 * 4096 * 9, 128 * 4096 * 9}};
        const cuuint32_t bd[4][4] = {{64, 96, 1, 1}, {64, 8, 2, 8}, {64, 8, 2, 8}, {64, 144, 1, 1}};
        for (int i = 0; i < 4; i++)
            enc(&prm.tm[p][i], CU_TENSOR_MAP_DATA_TYPE_BFLOAT16, 4, ptr[i], gd[i], gs[i], bd[i], es,
                CU_TENSOR_MAP_INTERLEAVE_NONE, CU_TENSOR_MAP_SWIZZLE_128B, CU_TENSOR_MAP_L2_PROMOTION_L2_128B,
                CU_TENSOR_MAP_FLOAT_OOB_FILL_NONE);
    }
    prm.out = (__nv_bfloat16*)d_out;
    gqa2_decode_kernel<<<128, NTHREADS, SM_TOTAL>>>(prm);
}
```

```cpp
#include <cuda_runtime.h>
#include <cuda_bf16.h>
#include <cuda.h>
#include <stdint.h>

namespace {

constexpr int TILE = 32768;
constexpr int NST  = 6;
constexpr int DEPTH = 4;
constexpr int NTHREADS = 384;

constexpr int SM_RING = 0;
constexpr int SM_SC   = NST * TILE;
constexpr int SM_P    = SM_SC + 16384;
constexpr int SM_Q    = SM_P;
constexpr int SM_X    = SM_P + 8192;
constexpr int SM_RED  = SM_X + 1152;
constexpr int SM_OF   = SM_RED + 512;
constexpr int SM_PROG = SM_OF + 256;
constexpr int SM_BAR  = SM_PROG + 16;
constexpr int SM_TOTAL = SM_BAR + 320 + 1024;

struct alignas(64) Params {
    CUtensorMap tm[2][4];
    const __nv_bfloat16* x[2];
    __nv_bfloat16* out;
};

struct alignas(4096) Scratch {
    float4 acc[4 * 40 * 72];
    float4 part[128 * 1024];
    uint4  q[128 * 8];
    float4 stat[128 * 16];
    unsigned int cnt[3 * 32];
};
__device__ Scratch g_s;

constexpr uint32_t SPIN_LIMIT = 1u << 22;

__device__ __forceinline__ void mbar_init(uint32_t a, uint32_t c) {
    asm volatile("mbarrier.init.shared::cta.b64 [%0], %1;" ::"r"(a), "r"(c) : "memory");
}
__device__ __forceinline__ void mbar_expect(uint32_t a, uint32_t b) {
    asm volatile("mbarrier.arrive.expect_tx.shared::cta.b64 _, [%0], %1;" ::"r"(a), "r"(b) : "memory");
}
__device__ __forceinline__ void mbar_arrive(uint32_t a) {
    asm volatile("mbarrier.arrive.shared::cta.b64 _, [%0];" ::"r"(a) : "memory");
}
__device__ __forceinline__ void mbar_wait(uint32_t a, uint32_t ph) {
    uint32_t ok, n = 0;
    do {
        asm volatile("{\n .reg .pred p;\n mbarrier.try_wait.parity.shared::cta.b64 p, [%1], %2;\n selp.u32 %0, 1, 0, p;\n}"
                     : "=r"(ok) : "r"(a), "r"(ph) : "memory");
        if (++n > SPIN_LIMIT) __trap();
    } while (!ok);
}
__device__ __forceinline__ bool mbar_test(uint32_t a, uint32_t ph) {
    uint32_t ok;
    asm volatile("{\n .reg .pred p;\n mbarrier.test_wait.parity.shared::cta.b64 p, [%1], %2;\n selp.u32 %0, 1, 0, p;\n}"
                 : "=r"(ok) : "r"(a), "r"(ph) : "memory");
    return __all_sync(0xffffffffu, ok != 0);
}
__device__ __forceinline__ void tma4d(uint32_t dst, const CUtensorMap* tm, int c0, int c1, int c3, uint32_t mbar, uint64_t pol) {
    asm volatile("cp.async.bulk.tensor.4d.shared::cluster.global.mbarrier::complete_tx::bytes.L2::cache_hint"
                 " [%0], [%1, {%3, %4, %5, %6}], [%2], %7;"
                 ::"r"(dst), "l"(tm), "r"(mbar), "r"(c0), "r"(c1), "r"(0), "r"(c3), "l"(pol) : "memory");
}
__device__ __forceinline__ void ldsm4(uint32_t (&r)[4], uint32_t a) {
    asm volatile("ldmatrix.sync.aligned.m8n8.x4.shared.b16 {%0,%1,%2,%3}, [%4];"
                 : "=r"(r[0]), "=r"(r[1]), "=r"(r[2]), "=r"(r[3]) : "r"(a) : "memory");
}
__device__ __forceinline__ void ldsm4t(uint32_t (&r)[4], uint32_t a) {
    asm volatile("ldmatrix.sync.aligned.m8n8.x4.trans.shared.b16 {%0,%1,%2,%3}, [%4];"
                 : "=r"(r[0]), "=r"(r[1]), "=r"(r[2]), "=r"(r[3]) : "r"(a) : "memory");
}
__device__ __forceinline__ void mma16816(float (&c)[4], const uint32_t (&a)[4], uint32_t b0, uint32_t b1) {
    asm volatile("mma.sync.aligned.m16n8k16.row.col.f32.bf16.bf16.f32 {%0,%1,%2,%3}, {%4,%5,%6,%7}, {%8,%9}, {%0,%1,%2,%3};"
                 : "+f"(c[0]), "+f"(c[1]), "+f"(c[2]), "+f"(c[3])
                 : "r"(a[0]), "r"(a[1]), "r"(a[2]), "r"(a[3]), "r"(b0), "r"(b1));
}
__device__ __forceinline__ uint4 lds128(uint32_t a) {
    uint4 v;
    asm volatile("ld.shared.v4.u32 {%0,%1,%2,%3}, [%4];" : "=r"(v.x), "=r"(v.y), "=r"(v.z), "=r"(v.w) : "r"(a) : "memory");
    return v;
}
__device__ __forceinline__ float4 lds128f(uint32_t a) {
    float4 v;
    asm volatile("ld.shared.v4.f32 {%0,%1,%2,%3}, [%4];" : "=f"(v.x), "=f"(v.y), "=f"(v.z), "=f"(v.w) : "r"(a) : "memory");
    return v;
}
__device__ __forceinline__ float2 lds64f(uint32_t a) {
    float2 v;
    asm volatile("ld.shared.v2.f32 {%0,%1}, [%2];" : "=f"(v.x), "=f"(v.y) : "r"(a) : "memory");
    return v;
}
__device__ __forceinline__ uint32_t lds32v(uint32_t a) {
    uint32_t v;
    asm volatile("ld.volatile.shared.u32 %0, [%1];" : "=r"(v) : "r"(a) : "memory");
    return v;
}
__device__ __forceinline__ void sts128(uint32_t a, uint4 v) {
    asm volatile("st.shared.v4.u32 [%0], {%1,%2,%3,%4};" ::"r"(a), "r"(v.x), "r"(v.y), "r"(v.z), "r"(v.w) : "memory");
}
__device__ __forceinline__ void sts64(uint32_t a, uint32_t x, uint32_t y) {
    asm volatile("st.shared.v2.u32 [%0], {%1,%2};" ::"r"(a), "r"(x), "r"(y) : "memory");
}
__device__ __forceinline__ void sts32(uint32_t a, uint32_t x) {
    asm volatile("st.volatile.shared.u32 [%0], %1;" ::"r"(a), "r"(x) : "memory");
}
__device__ __forceinline__ void poll128(uint4& v, const void* p, bool pred) {
    asm volatile("{\n .reg .pred p;\n setp.ne.u32 p, %5, 0;\n @p ld.relaxed.gpu.global.v4.u32 {%0,%1,%2,%3}, [%4];\n}"
                 : "+r"(v.x), "+r"(v.y), "+r"(v.z), "+r"(v.w) : "l"(p), "r"((uint32_t)pred) : "memory");
}
__device__ __forceinline__ void stg128(void* p, uint4 v) {
    asm volatile("st.relaxed.gpu.global.v4.u32 [%0], {%1,%2,%3,%4};" ::"l"(p), "r"(v.x), "r"(v.y), "r"(v.z), "r"(v.w) : "memory");
}
__device__ __forceinline__ void stg64(void* p, uint32_t x, uint32_t y) {
    asm volatile("st.relaxed.gpu.global.v2.u32 [%0], {%1,%2};" ::"l"(p), "r"(x), "r"(y) : "memory");
}
__device__ __forceinline__ void stg32(void* p, uint32_t x) {
    asm volatile("st.relaxed.gpu.global.u32 [%0], %1;" ::"l"(p), "r"(x) : "memory");
}
__device__ __forceinline__ uint32_t nz(float f) {
    uint32_t u = __float_as_uint(f);
    return u == 0u ? 0x80000000u : u;
}
__device__ __forceinline__ bool all_set(const uint4& v) { return v.x != 0u && v.y != 0u && v.z != 0u && v.w != 0u; }
__device__ __forceinline__ void poll2(uint4& a, const void* pa, uint4& b, const void* pb, int sleep_ns) {
    uint32_t n = 0;
    while (true) {
        const bool ma = !all_set(a), mb = !all_set(b);
        if (!__any_sync(0xffffffffu, ma || mb)) break;
        if (sleep_ns && n) __nanosleep(sleep_ns);
        poll128(a, pa, ma);
        poll128(b, pb, mb);
        if (++n > SPIN_LIMIT) __trap();
    }
}
__device__ __forceinline__ uint32_t pack_bf16(float lo, float hi) {
    uint32_t r;
    asm("cvt.rn.bf16x2.f32 %0, %1, %2;" : "=r"(r) : "f"(hi), "f"(lo));
    return r;
}
__device__ __forceinline__ float ex2(float x) {
    float r;
    asm("ex2.approx.ftz.f32 %0, %1;" : "=f"(r) : "f"(x));
    return r;
}
__device__ __forceinline__ float sel4(const float (&c)[4], int j) {
    float a = (j & 1) ? c[1] : c[0];
    float b = (j & 1) ? c[3] : c[2];
    return (j & 2) ? b : a;
}
__device__ __forceinline__ bool elect_one() {
    uint32_t p;
    asm volatile("{\n .reg .pred p;\n elect.sync _|p, 0xffffffff;\n selp.u32 %0, 1, 0, p;\n}" : "=r"(p));
    return p != 0;
}
__device__ __forceinline__ void bar_consumers() { asm volatile("bar.sync 1, 256;" ::: "memory"); }

__global__ void __launch_bounds__(NTHREADS, 1)
gqa2_decode_kernel(const __grid_constant__ Params prm) {
    extern __shared__ unsigned char smem_raw[];
    const uint32_t sb = ((uint32_t)__cvta_generic_to_shared(smem_raw) + 1023u) & ~1023u;
    const int tid = threadIdx.x, warp = tid >> 5, lane = tid & 31;
    const int bid = blockIdx.x, prob = bid >> 6, c = bid & 63;
    const uint32_t bar_full = sb + SM_BAR, bar_wo = bar_full + 16 * NST, bar_empty = bar_wo + 32;
    const uint32_t bar_ready = bar_empty + 8 * NST, bar_x = bar_ready + 8, bar_of = bar_ready + 16,
                   bar_go = bar_ready + 24, bar_ofa = bar_ready + 56;

    int wu = __shfl_sync(0xffffffffu, warp, 0);
    if (wu == 8) {
        uint64_t pol;
        asm volatile("createpolicy.fractional.L2::evict_first.b64 %0, 1.0;" : "=l"(pol));
        if (elect_one()) {
#pragma unroll
            for (int s = 0; s < 2 * NST; s++) mbar_init(bar_full + 8 * s, 1);
            asm volatile("fence.mbarrier_init.release.cluster;" ::: "memory");
#pragma unroll
            for (int n = 0; n < DEPTH; n++) {
                mbar_expect(bar_full + 8 * n, 12288);
                tma4d(sb + SM_RING + (n >> 1) * TILE + (n & 1) * 12288, &prm.tm[prob][0], c * 64, n * 96, 0, bar_full + 8 * n, pol);
            }
#pragma unroll
            for (int s = 0; s < 4; s++) mbar_init(bar_wo + 8 * s, 1);
#pragma unroll
            for (int s = 0; s < NST; s++) mbar_init(bar_empty + 8 * s, 8);
#pragma unroll
            for (int s = 0; s < 7; s++) mbar_init(bar_ready + 8 * s, s == 2 ? 2 : 1);
            mbar_init(bar_ofa, 6);
            asm volatile("fence.mbarrier_init.release.cluster;" ::: "memory");
            mbar_expect(bar_x, 1152);
            asm volatile("cp.async.bulk.shared::cluster.global.mbarrier::complete_tx::bytes [%0], [%1], 1152, [%2];"
                         ::"r"(sb + SM_X), "l"(prm.x[prob]), "r"(bar_x) : "memory");
            sts64(sb + SM_PROG, 0u, 0u);
#pragma unroll
            for (int k = 1; k < 4; k++) asm volatile("prefetch.tensormap [%0];" ::"l"(&prm.tm[prob][k]) : "memory");
        }
        __syncwarp();
        asm volatile("bar.arrive 3, %0;" ::"n"(NTHREADS) : "memory");
        int ib = DEPTH, iph = 0;
        int nw = 0, wb = 0, wph = 0;
#pragma unroll 1
        for (int n = DEPTH; n < 70; n++) {
            const bool kv = n >= 6;
            const int bytes = kv ? TILE / 2 : 12288;
            const uint32_t dst = sb + SM_RING + (ib >> 1) * TILE + (ib & 1) * bytes, bar = bar_full + 8 * ib;
            if (n >= 2 * NST && (n & 1) == 0) mbar_wait(bar_empty + 4 * ib, iph ^ 1);
            if (elect_one()) mbar_expect(bar, bytes);
            while (true) {
                int win = DEPTH;
                if (n >= 14) {
                    const int lag = (int)lds32v(sb + SM_PROG) - ((n - 10) * 128 - 256);
                    win = min(max(DEPTH + (lag >> 7), 2), 8);
                }
                if (n - nw < win) break;
                mbar_wait(bar_full + 8 * wb, wph);
                nw++;
                if (++wb == 2 * NST) { wb = 0; wph ^= 1; }
            }
            if (elect_one()) {
                tma4d(dst, &prm.tm[prob][kv + (n >= 38)], kv ? 0 : c * 64, kv ? 0 : n * 96, kv ? ((n - 6) & 31) * 512 + c * 8 : 0, bar, pol);
                if (n >= 10) sts32(sb + SM_PROG + 4, n - 9);
            }
            if (++ib == 2 * NST) { ib = 0; iph ^= 1; }
        }
#pragma unroll
        for (int k = 0; k < 4; k++) {
            if (k == 0) mbar_wait(bar_empty + 40, 0);
            else if (k < 3) mbar_wait(bar_empty + 8 * (k - 1), 1);
            for (int w = 6; w >= 2; w--) {
                const int m = 70 + k - w;
                mbar_wait(bar_full + 8 * (m < 70 ? m - 60 : m - 58), m < 70 ? 1 : 0);
                const int lag = (int)lds32v(sb + SM_PROG) - ((60 + k) * 128 - 256);
                if (w <= DEPTH + (lag >> 7)) break;
            }
            if (elect_one()) sts32(sb + SM_PROG + 4, 61 + k);
            if (elect_one())
                tma4d(sb + SM_RING + (k ? (k - 1) * 18432 : 5 * TILE), &prm.tm[prob][3], 0, (k * 1024 + c * 16) * 9, 0, bar_wo + 8 * k, pol);
        }
    } else {
        asm volatile("bar.sync 3, %0;" ::"n"(NTHREADS) : "memory");
    }
    asm volatile("" : "+r"(wu));
    const int g8 = lane >> 2, j4 = lane & 3, l8 = lane & 7, m4 = lane >> 3;
    const uint4 zero4 = make_uint4(0u, 0u, 0u, 0u);

    if (wu > 8) {
        if (wu < 11) {
            const int hf = wu - 9;
            float4* const psrc = g_s.part + bid * 1024 + hf * 128 + lane;
#pragma unroll
            for (int i = 0; i < 16; i++) { stg128(psrc + (i >> 2) * 256 + (i & 3) * 32, zero4); __nanosleep(300); }
            if (hf == 0) {
                const int e = c * 5 + lane;
                if (lane < 5) stg128(g_s.acc + (prob * 40 + (e >> 3)) * 72 + (e & 7), zero4);
            } else if (lane < 16) stg128(g_s.stat + bid * 16 + lane, zero4);
            asm volatile("bar.sync 2, 64;" ::: "memory");
            if (tid == 288) {
                unsigned int v, n = 0;
                asm volatile("atom.release.gpu.global.add.u32 %0, [%1], 1;" : "=r"(v) : "l"(g_s.cnt + prob * 32) : "memory");
                const unsigned int target = (v & ~63u) + 64u;
                do {
                    __nanosleep(n ? 1000 : 3000);
                    asm volatile("ld.relaxed.gpu.global.u32 %0, [%1];" : "=r"(v) : "l"(g_s.cnt + prob * 32) : "memory");
                    if (++n > SPIN_LIMIT) __trap();
                } while ((int)(v - target) < 0);
                asm volatile("ld.acquire.gpu.global.u32 %0, [%1];" : "=r"(v) : "l"(g_s.cnt + prob * 32) : "memory");
                mbar_arrive(bar_ready);
            }
            __syncwarp();
            mbar_wait(bar_go, 0);
            float e[4];
            {
                uint4 sa = zero4, sb2 = zero4, sc = zero4, sd = zero4;
                const float4* ssrc = g_s.stat + ((prob * 2 + ((c >> 3) & 1)) * 16 + 4 * m4 + (c >> 4)) * 32 + l8;
                poll128(sc, ssrc + 16 * (1 - hf), true);
                poll128(sd, ssrc + 16 * (1 - hf) + 8, true);
                poll2(sa, ssrc + 16 * hf, sb2, ssrc + 16 * hf + 8, 300);
                poll2(sc, ssrc + 16 * (1 - hf), sd, ssrc + 16 * (1 - hf) + 8, 300);
                if (hf == 0 && lane < 8) stg128(g_s.q + bid * 8 + lane, zero4);
                float M = fmaxf(fmaxf(fmaxf(__uint_as_float(sa.x), __uint_as_float(sa.z)), fmaxf(__uint_as_float(sb2.x), __uint_as_float(sb2.z))),
                                fmaxf(fmaxf(__uint_as_float(sc.x), __uint_as_float(sc.z)), fmaxf(__uint_as_float(sd.x), __uint_as_float(sd.z))));
#pragma unroll
                for (int o = 4; o > 0; o >>= 1) M = fmaxf(M, __shfl_xor_sync(0xffffffffu, M, o));
                e[0] = ex2(__uint_as_float(sa.x) - M); e[1] = ex2(__uint_as_float(sa.z) - M);
                e[2] = ex2(__uint_as_float(sb2.x) - M); e[3] = ex2(__uint_as_float(sb2.z) - M);
                const float La = (e[0] * __uint_as_float(sa.y) + e[1] * __uint_as_float(sa.w)) + (e[2] * __uint_as_float(sb2.y) + e[3] * __uint_as_float(sb2.w));
                const float Lb = (ex2(__uint_as_float(sc.x) - M) * __uint_as_float(sc.y) + ex2(__uint_as_float(sc.z) - M) * __uint_as_float(sc.w)) +
                                 (ex2(__uint_as_float(sd.x) - M) * __uint_as_float(sd.y) + ex2(__uint_as_float(sd.z) - M) * __uint_as_float(sd.w));
                float L = La + Lb;
#pragma unroll
                for (int o = 4; o > 0; o >>= 1) L += __shfl_xor_sync(0xffffffffu, L, o);
                const float inv = 1.0f / L;
#pragma unroll
                for (int i = 0; i < 4; i++) e[i] *= inv;
            }
            const bool up = lane >= 16;
            const int pr = 2 * j4 + (up ? 1 : 0);
            const uint32_t of_addr = sb + SM_OF + hf * 128 + ((pr & 3) * 8 + (pr >> 2)) * 4;
#pragma unroll 1
            for (int t = 0; t < 4; t++) {
                float wg[4];
#pragma unroll
                for (int i = 0; i < 4; i++) {
                    const float u0 = __shfl_sync(0xffffffffu, e[i & 2], 8 * t + 4 * (i & 1) + (g8 >> 1));
                    const float u1 = __shfl_sync(0xffffffffu, e[(i & 2) + 1], 8 * t + 4 * (i & 1) + (g8 >> 1));
                    wg[i] = (g8 & 1) ? u1 : u0;
                }
                mbar_wait(bar_go + 8 * t, 0);
                uint4 pv[4] = {zero4, zero4, zero4, zero4};
                {
                    uint32_t n = 0;
                    while (true) {
                        bool m[4], miss = false;
#pragma unroll
                        for (int i = 0; i < 4; i++) { m[i] = !all_set(pv[i]); miss |= m[i]; }
                        if (!__any_sync(0xffffffffu, miss)) break;
                        if (t < 3 && n) __nanosleep(300);
#pragma unroll
                        for (int i = 0; i < 4; i++) poll128(pv[i], psrc + 256 * t + 32 * i, m[i]);
                        if (++n > SPIN_LIMIT) __trap();
                    }
                }
                const float x = (wg[0] * __uint_as_float(pv[0].x) + wg[1] * __uint_as_float(pv[1].x)) + (wg[2] * __uint_as_float(pv[2].x) + wg[3] * __uint_as_float(pv[3].x));
                const float y = (wg[0] * __uint_as_float(pv[0].y) + wg[1] * __uint_as_float(pv[1].y)) + (wg[2] * __uint_as_float(pv[2].y) + wg[3] * __uint_as_float(pv[3].y));
                const float z = (wg[0] * __uint_as_float(pv[0].z) + wg[1] * __uint_as_float(pv[1].z)) + (wg[2] * __uint_as_float(pv[2].z) + wg[3] * __uint_as_float(pv[3].z));
                const float w = (wg[0] * __uint_as_float(pv[0].w) + wg[1] * __uint_as_float(pv[1].w)) + (wg[2] * __uint_as_float(pv[2].w) + wg[3] * __uint_as_float(pv[3].w));
                float k0 = (up ? z : x) + __shfl_xor_sync(0xffffffffu, up ? x : z, 16);
                float k1 = (up ? w : y) + __shfl_xor_sync(0xffffffffu, up ? y : w, 16);
#pragma unroll
                for (int o = 8; o > 2; o >>= 1) {
                    k0 += __shfl_xor_sync(0xffffffffu, k0, o);
                    k1 += __shfl_xor_sync(0xffffffffu, k1, o);
                }
                if ((lane & 12) == 0) sts32(of_addr + 8 * t, pack_bf16(k0, k1));
                __syncwarp();
                if (lane == 0) mbar_arrive(t < 3 ? bar_ofa : bar_of);
            }
        } else {
            if (lane < 4) mbar_expect(bar_wo + 8 * lane, 18432);
            if (lane == 0) {
                uint32_t rep = 0, n = 0;
                while (rep < 64u) {
                    const uint32_t cur = lds32v(sb + SM_PROG + 4);
                    if (cur == rep) { __nanosleep(40); if (++n > (SPIN_LIMIT << 2)) __trap(); continue; }
                    uint32_t v;
                    asm volatile("atom.relaxed.gpu.global.add.u32 %0, [%1], %2;" : "=r"(v) : "l"(g_s.cnt + 64), "r"(cur - rep) : "memory");
                    sts32(sb + SM_PROG, v);
                    if (v + (cur - rep) == 128u * 64u) stg32(g_s.cnt + 64, 0u);
                    rep = cur;
                }
            }
        }
        return;
    } else if (wu < 8) {
        {
            uint32_t xb[3][12];
            mbar_wait(bar_x, 0);
#pragma unroll
            for (int b = 0; b < 3; b++)
#pragma unroll
                for (int t = 0; t < 12; t++) xb[b][t] = lds32v(sb + SM_X + ((warp >> 2) * 48 + j4 + b * 96 + 4 * t) * 4);
            float c0[4] = {0.f, 0.f, 0.f, 0.f}, c1[4] = {0.f, 0.f, 0.f, 0.f};
            const uint32_t base = sb + SM_RING + ((warp >> 2) * 96 + (m4 >> 1) * 8 + l8) * 128 + (((2 * (warp & 3) + (m4 & 1)) ^ l8) << 4);
#pragma unroll
            for (int b = 0; b < 3; b++) {
                mbar_wait(bar_full + 16 * b + 8 * (warp >> 2), 0);
#pragma unroll
                for (int t = 0; t < 3; t++) {
                    uint32_t a0[4], a1[4];
                    ldsm4t(a0, base + b * TILE + (2 * t) * 2048);
                    ldsm4t(a1, base + b * TILE + (2 * t + 1) * 2048);
                    mma16816(c0, a0, xb[b][4 * t], xb[b][4 * t + 1]);
                    mma16816(c1, a1, xb[b][4 * t + 2], xb[b][4 * t + 3]);
                }
                __syncwarp();
                if (lane == 0) mbar_arrive(bar_empty + 8 * b);
            }
            if (j4 < 2) sts32(sb + SM_RED + (warp * 16 + g8 + 8 * j4) * 4, __float_as_uint(j4 ? c0[2] + c1[2] : c0[0] + c1[0]));
        }
        bar_consumers();
        if (warp == 0) {
            const float2 va = lds64f(sb + SM_RED + lane * 8), vb = lds64f(sb + SM_RED + 256 + lane * 8);
            uint32_t u = pack_bf16(va.x + vb.x, va.y + vb.y);
            if (u == 0u) u = 0x8000u;
            const int d = 64 * (c & 1) + 2 * lane;
            const int w16 = 2 * (d >> 4) + ((d >> 3) & 1);
            stg32(reinterpret_cast<uint32_t*>(g_s.q) + (bid >> 2) * 128 + (w16 >> 2) * 32 + ((c >> 1) & 1) * 16 + ((d & 7) >> 1) * 4 + (w16 & 3), u);
        }
        {
            uint4 v = zero4, v2 = zero4;
            mbar_wait(bar_full + 8 * 9, 0);
            poll2(v, g_s.q + prob * 512 + tid, v2, g_s.q + prob * 512 + 256 + tid, 300);
            sts128(sb + SM_Q + tid * 16, v);
            sts128(sb + SM_Q + 4096 + tid * 16, v2);
        }
        bar_consumers();
        const uint32_t frag_off = (g8 & 1) * 64 + j4 * 16;
        int s = 3, ph = 0;

        {
            const uint32_t kbase = sb + SM_RING + (2 * warp + (m4 & 1)) * 2048 + l8 * 128 + (((m4 >> 1) ^ l8) << 4);
            const uint32_t sc_addr = sb + SM_SC + (warp * 32 + (j4 & 1) * 16 + (g8 >> 1) * 4 + (g8 & 1) + (j4 >> 1) * 2) * 4;
#pragma unroll 1
            for (int i = 0; i < 16; i++) {
                uint4 qb[4];
#pragma unroll
                for (int q = 0; q < 4; q++) qb[q] = lds128(sb + SM_Q + i * 512 + q * 128 + frag_off);
                mbar_wait(bar_full + 16 * s + 8 * (warp >> 2), ph);
                float c0[4] = {0.f, 0.f, 0.f, 0.f}, c1[4] = {0.f, 0.f, 0.f, 0.f};
                const uint32_t kb = kbase + s * TILE;
#pragma unroll
                for (int q = 0; q < 4; q++) {
                    uint32_t a0[4], a1[4];
                    ldsm4(a0, (kb ^ (((2 * q) & 3) << 5)) + (q >> 1) * 1024);
                    ldsm4(a1, (kb ^ (((2 * q + 1) & 3) << 5)) + (q >> 1) * 1024);
                    mma16816(c0, a0, qb[q].x, qb[q].y);
                    mma16816(c1, a1, qb[q].z, qb[q].w);
                }
                __syncwarp();
                if (lane == 0) mbar_arrive(bar_empty + 8 * s);
                sts32(sc_addr + i * 1024, __float_as_uint(sel4(c0, j4) + sel4(c1, j4)));
                if (++s == NST) { s = 0; ph ^= 1; }
            }
        }
        mbar_wait(bar_ready, 0);
        bar_consumers();

        {
            constexpr float SCALE = 0.08838834764831845f * 1.4426950408889634f;
            const int hd = warp & 1, st = warp >> 1;
            float4 sv[4];
            float ms[4], sum[4];
#pragma unroll
            for (int t = 0; t < 4; t++) {
                sv[t] = lds128f(sb + SM_SC + ((4 * st + t) * 256 + g8 * 32 + hd * 16 + j4 * 4) * 4);
                ms[t] = fmaxf(fmaxf(sv[t].x, sv[t].y), fmaxf(sv[t].z, sv[t].w));
            }
#pragma unroll
            for (int o = 16; o > 0; o >>= 1)
#pragma unroll
                for (int t = 0; t < 4; t++) ms[t] = fmaxf(ms[t], __shfl_xor_sync(0xffffffffu, ms[t], o));
#pragma unroll
            for (int t = 0; t < 4; t++) {
                ms[t] *= SCALE;
                const float m = ms[t];
                const float p0 = ex2(fmaf(sv[t].x, SCALE, -m)), p1 = ex2(fmaf(sv[t].y, SCALE, -m));
                const float p2 = ex2(fmaf(sv[t].z, SCALE, -m)), p3 = ex2(fmaf(sv[t].w, SCALE, -m));
                sum[t] = (p0 + p1) + (p2 + p3);
                sts64(sb + SM_P + (4 * st + t) * 512 + (g8 >> 1) * 128 + hd * 64 + j4 * 16 + (g8 & 1) * 8, pack_bf16(p0, p1), pack_bf16(p2, p3));
            }
            bar_consumers();
#pragma unroll
            for (int o = 16; o > 0; o >>= 1)
#pragma unroll
                for (int t = 0; t < 4; t++) sum[t] += __shfl_xor_sync(0xffffffffu, sum[t], o);
            if (lane < 4)
                stg64(reinterpret_cast<float2*>(g_s.stat) + ((prob * 2 + hd) * 16 + 4 * st + lane) * 64 + c, nz(sel4(ms, lane)), nz(sel4(sum, lane)));
        }

        {
            const uint32_t vbase = sb + SM_RING + (m4 >> 1) * 2048 + (warp >> 2) * 1024 + l8 * 128 + (((2 * (warp & 3) + (m4 & 1)) ^ l8) << 4);
            float* const dst = reinterpret_cast<float*>(g_s.part) + (prob * 64 + 8 * (j4 & 1) + warp) * 4096 + c * 16 + g8 + 8 * (j4 >> 1);
            const int go_off = 3 + (c >> 4);
#pragma unroll 1
            for (int i = 0; i < 16; i++) {
                float c0[4] = {0.f, 0.f, 0.f, 0.f}, c1[4] = {0.f, 0.f, 0.f, 0.f};
                uint4 pb[4];
#pragma unroll
                for (int q = 0; q < 4; q++) pb[q] = lds128(sb + SM_P + i * 512 + q * 128 + frag_off);
                const uint32_t vb = vbase + s * TILE;
#pragma unroll
                for (int q = 0; q < 4; q++) {
                    uint32_t a0[4], a1[4];
                    if ((q & 1) == 0) mbar_wait(bar_full + 16 * s + 4 * q, ph);
                    ldsm4t(a0, vb + (2 * q) * 4096);
                    ldsm4t(a1, vb + (2 * q + 1) * 4096);
                    mma16816(c0, a0, pb[q].x, pb[q].y);
                    mma16816(c1, a1, pb[q].z, pb[q].w);
                }
                __syncwarp();
                if (lane == 0) mbar_arrive(bar_empty + 8 * s);
                stg32(dst + (i & 3) * (16 * 4096) + (i >> 2) * 1024, nz(sel4(c0, j4) + sel4(c1, j4)));
                if (tid == 0 && (i == 15 || (i >= go_off && ((i - go_off) & 3) == 0)))
                    mbar_arrive(bar_go + (i == 15 ? 24 : 2 * (i - go_off)));
                if (++s == NST) { s = 0; ph ^= 1; }
            }
        }
    }

    {
        float acc[2][4][4];
#pragma unroll
        for (int e = 0; e < 32; e++) (&acc[0][0][0])[e] = 0.f;
        const int rho = 9 * ((m4 >> 1) * 8 + l8) + warp;
        uint32_t base[4];
#pragma unroll
        for (int mt = 0; mt < 4; mt++) base[mt] = (sb + SM_RING + rho * 128 + (((m4 & 1) ^ (rho & 7)) << 4)) ^ (mt << 5);
        float4* dst = g_s.acc + (prob * 40 + (tid >> 3)) * 72 + (tid & 7);
        __nv_bfloat16* optr = prm.out + prob * 576 + warp * 64 + 16 * j4 + g8;
        uint32_t js = j4, of_addr = sb + SM_OF + (g8 & 1) * 128 + j4 * 32;
        asm volatile("" : "+r"(base[0]), "+r"(base[1]), "+r"(base[2]), "+r"(base[3]), "+l"(dst), "+l"(optr), "+r"(js), "+r"(of_addr));
        uint32_t wa[2][4][4];
#define LOAD_W(t) _Pragma("unroll") for (int mt = 0; mt < 4; mt++) ldsm4t(wa[(t) & 1][mt], base[mt] + ((t) ? ((t) - 1) * 18432 : 5 * TILE))
#define MMA_W(t, b0, b1) _Pragma("unroll") for (int mt = 0; mt < 4; mt++) mma16816(acc[(t) & 1][mt], wa[(t) & 1][mt], b0, b1)
        auto pick = [&](int a, int e) {
            float r;
            asm("{\n .reg .pred p, q;\n .reg .f32 u, v;\n .reg .b32 t;\n and.b32 t, %5, 1;\n setp.ne.u32 p, t, 0;\n setp.gt.u32 q, %5, 1;\n"
                " selp.f32 u, %2, %1, p;\n selp.f32 v, %4, %3, p;\n selp.f32 %0, v, u, q;\n}"
                : "=f"(r) : "f"(acc[a][0][e]), "f"(acc[a][1][e]), "f"(acc[a][2][e]), "f"(acc[a][3][e]), "r"(js));
            return r;
        };
        mbar_wait(bar_ofa, 0);
        const uint4 o0 = lds128(of_addr);
        const float2 o1 = lds64f(of_addr + 16);
        mbar_wait(bar_wo, 0);
        LOAD_W(0);
        MMA_W(0, o0.x, o0.y);
        mbar_wait(bar_wo + 8, 0);
        LOAD_W(1);
        MMA_W(1, o0.z, o0.w);
        mbar_wait(bar_wo + 16, 0);
        LOAD_W(2);
        const bool have_w = mbar_test(bar_wo + 24, 0);
        if (have_w) { LOAD_W(3); }
        MMA_W(2, __float_as_uint(o1.x), __float_as_uint(o1.y));
        float2 o2;
        bool have_o = false;
        if (!have_w) {
            uint32_t n = 0;
            while (!mbar_test(bar_wo + 24, 0)) {
                if (mbar_test(bar_of, 0)) {
                    o2 = lds64f(of_addr + 24);
                    have_o = true;
                    mbar_wait(bar_wo + 24, 0);
                    break;
                }
                if (++n > (SPIN_LIMIT << 4)) __trap();
            }
            LOAD_W(3);
        }
        if (!have_o) { mbar_wait(bar_of, 0); o2 = lds64f(of_addr + 24); }
        MMA_W(3, __float_as_uint(o2.x), __float_as_uint(o2.y));
        const float v0 = (pick(0, 0) + pick(0, 1)) + (pick(1, 0) + pick(1, 1)), v1 = (pick(0, 2) + pick(0, 3)) + (pick(1, 2) + pick(1, 3));
        float r0, r1, r2;
        asm volatile("{\n .reg .f32 t;\n atom.relaxed.gpu.global.add.v4.f32 {%0,%1,%2,t}, [%3], {%4,%5,%6,%7};\n}"
                     : "=f"(r0), "=f"(r1), "=f"(r2) : "l"(dst), "f"(v0), "f"(v1), "f"(1.0f), "f"(0.0f) : "memory");
        if (r2 == 63.0f) { optr[0] = __float2bfloat16(r0 + v0); optr[8] = __float2bfloat16(r1 + v1); }
#undef LOAD_W
#undef MMA_W
    }
}

typedef CUresult (*EncodeFn)(CUtensorMap*, CUtensorMapDataType, cuuint32_t, void*, const cuuint64_t*, const cuuint64_t*,
                             const cuuint32_t*, const cuuint32_t*, CUtensorMapInterleave, CUtensorMapSwizzle,
                             CUtensorMapL2promotion, CUtensorMapFloatOOBfill);

}

extern "C" void kernel_launch(void* const* d_in, const int* in_sizes, int n_in, void* d_out, int out_size) {
    (void)in_sizes; (void)n_in; (void)out_size;
    static EncodeFn enc = nullptr;
    if (!enc) {
        cudaDriverEntryPointQueryResult qr;
        void* fn = nullptr;
        cudaGetDriverEntryPoint("cuTensorMapEncodeTiled", &fn, cudaEnableDefault, &qr);
        enc = (EncodeFn)fn;
        cudaFuncSetAttribute(gqa2_decode_kernel, cudaFuncAttributeMaxDynamicSharedMemorySize, SM_TOTAL);
    }
    Params prm;
    const cuuint32_t es[4] = {1, 1, 1, 1};
    for (int p = 0; p < 2; p++) {
        prm.x[p] = (const __nv_bfloat16*)d_in[5 * p + 0];
        void* ptr[4] = {d_in[5 * p + 3], d_in[5 * p + 1], d_in[5 * p + 2], d_in[5 * p + 4]};
        const cuuint64_t gd[4][4] = {{4096, 576, 1, 1}, {64, 8, 2, 16 * 8192 / 8}, {64, 8, 2, 16 * 8192 / 8}, {64, 4096 * 9, 1, 1}};
        const cuuint64_t gs[4][3] = {{8192, 8192 * 576, 8192 * 576}, {256, 128, 2048}, {256, 128, 2048}, {128, 128 * 4096 * 9, 128 * 4096 * 9}};
        const cuuint32_t bd[4][4] = {{64, 96, 1, 1}, {64, 8, 2, 8}, {64, 8, 2, 8}, {64, 144, 1, 1}};
        for (int i = 0; i < 4; i++)
            enc(&prm.tm[p][i], CU_TENSOR_MAP_DATA_TYPE_BFLOAT16, 4, ptr[i], gd[i], gs[i], bd[i], es,
                CU_TENSOR_MAP_INTERLEAVE_NONE, CU_TENSOR_MAP_SWIZZLE_128B, CU_TENSOR_MAP_L2_PROMOTION_L2_128B,
                CU_TENSOR_MAP_FLOAT_OOB_FILL_NONE);
    }
    prm.out = (__nv_bfloat16*)d_out;
    gqa2_decode_kernel<<<128, NTHREADS, SM_TOTAL>>>(prm);
}
```

```cpp
#include <cuda_runtime.h>
#include <cuda_bf16.h>
#include <cuda.h>
#include <stdint.h>

namespace {

constexpr int TILE = 32768;
constexpr int NST  = 6;
constexpr int DEPTH = 4;
constexpr int NTHREADS = 384;

constexpr int SM_RING = 0;
constexpr int SM_SC   = NST * TILE;
constexpr int SM_P    = SM_SC + 16384;
constexpr int SM_Q    = SM_P;
constexpr int SM_X    = SM_P + 8192;
constexpr int SM_RED  = SM_X + 1152;
constexpr int SM_OF   = SM_RED + 512;
constexpr int SM_PROG = SM_OF + 256;
constexpr int SM_BAR  = SM_PROG + 16;
constexpr int SM_TOTAL = SM_BAR + 320 + 1024;

struct alignas(64) Params {
    CUtensorMap tm[2][4];
    const __nv_bfloat16* x[2];
    __nv_bfloat16* out;
};

struct alignas(4096) Scratch {
    float4 acc[4 * 40 * 72];
    float4 part[128 * 1024];
    uint4  q[128 * 8];
    float4 stat[128 * 16];
    unsigned int cnt[3 * 32];
};
__device__ Scratch g_s;

constexpr uint32_t SPIN_LIMIT = 1u << 22;

__device__ __forceinline__ void mbar_init(uint32_t a, uint32_t c) {
    asm volatile("mbarrier.init.shared::cta.b64 [%0], %1;" ::"r"(a), "r"(c) : "memory");
}
__device__ __forceinline__ void mbar_expect(uint32_t a, uint32_t b) {
    asm volatile("mbarrier.arrive.expect_tx.shared::cta.b64 _, [%0], %1;" ::"r"(a), "r"(b) : "memory");
}
__device__ __forceinline__ void mbar_arrive(uint32_t a) {
    asm volatile("mbarrier.arrive.shared::cta.b64 _, [%0];" ::"r"(a) : "memory");
}
__device__ __forceinline__ void mbar_wait(uint32_t a, uint32_t ph) {
    uint32_t ok, n = 0;
    do {
        asm volatile("{\n .reg .pred p;\n mbarrier.try_wait.parity.shared::cta.b64 p, [%1], %2;\n selp.u32 %0, 1, 0, p;\n}"
                     : "=r"(ok) : "r"(a), "r"(ph) : "memory");
        if (++n > SPIN_LIMIT) __trap();
    } while (!ok);
}
__device__ __forceinline__ bool mbar_test(uint32_t a, uint32_t ph) {
    uint32_t ok;
    asm volatile("{\n .reg .pred p;\n mbarrier.test_wait.parity.shared::cta.b64 p, [%1], %2;\n selp.u32 %0, 1, 0, p;\n}"
                 : "=r"(ok) : "r"(a), "r"(ph) : "memory");
    return __all_sync(0xffffffffu, ok != 0);
}
__device__ __forceinline__ void tma4d(uint32_t dst, const CUtensorMap* tm, int c0, int c1, int c3, uint32_t mbar, uint64_t pol) {
    asm volatile("cp.async.bulk.tensor.4d.shared::cluster.global.mbarrier::complete_tx::bytes.L2::cache_hint"
                 " [%0], [%1, {%3, %4, %5, %6}], [%2], %7;"
                 ::"r"(dst), "l"(tm), "r"(mbar), "r"(c0), "r"(c1), "r"(0), "r"(c3), "l"(pol) : "memory");
}
__device__ __forceinline__ void ldsm4(uint32_t (&r)[4], uint32_t a) {
    asm volatile("ldmatrix.sync.aligned.m8n8.x4.shared.b16 {%0,%1,%2,%3}, [%4];"
                 : "=r"(r[0]), "=r"(r[1]), "=r"(r[2]), "=r"(r[3]) : "r"(a) : "memory");
}
__device__ __forceinline__ void ldsm4t(uint32_t (&r)[4], uint32_t a) {
    asm volatile("ldmatrix.sync.aligned.m8n8.x4.trans.shared.b16 {%0,%1,%2,%3}, [%4];"
                 : "=r"(r[0]), "=r"(r[1]), "=r"(r[2]), "=r"(r[3]) : "r"(a) : "memory");
}
__device__ __forceinline__ void mma16816(float (&c)[4], const uint32_t (&a)[4], uint32_t b0, uint32_t b1) {
    asm volatile("mma.sync.aligned.m16n8k16.row.col.f32.bf16.bf16.f32 {%0,%1,%2,%3}, {%4,%5,%6,%7}, {%8,%9}, {%0,%1,%2,%3};"
                 : "+f"(c[0]), "+f"(c[1]), "+f"(c[2]), "+f"(c[3])
                 : "r"(a[0]), "r"(a[1]), "r"(a[2]), "r"(a[3]), "r"(b0), "r"(b1));
}
__device__ __forceinline__ uint4 lds128(uint32_t a) {
    uint4 v;
    asm volatile("ld.shared.v4.u32 {%0,%1,%2,%3}, [%4];" : "=r"(v.x), "=r"(v.y), "=r"(v.z), "=r"(v.w) : "r"(a) : "memory");
    return v;
}
__device__ __forceinline__ float4 lds128f(uint32_t a) {
    float4 v;
    asm volatile("ld.shared.v4.f32 {%0,%1,%2,%3}, [%4];" : "=f"(v.x), "=f"(v.y), "=f"(v.z), "=f"(v.w) : "r"(a) : "memory");
    return v;
}
__device__ __forceinline__ float2 lds64f(uint32_t a) {
    float2 v;
    asm volatile("ld.shared.v2.f32 {%0,%1}, [%2];" : "=f"(v.x), "=f"(v.y) : "r"(a) : "memory");
    return v;
}
__device__ __forceinline__ uint32_t lds32v(uint32_t a) {
    uint32_t v;
    asm volatile("ld.volatile.shared.u32 %0, [%1];" : "=r"(v) : "r"(a) : "memory");
    return v;
}
__device__ __forceinline__ void sts128(uint32_t a, uint4 v) {
    asm volatile("st.shared.v4.u32 [%0], {%1,%2,%3,%4};" ::"r"(a), "r"(v.x), "r"(v.y), "r"(v.z), "r"(v.w) : "memory");
}
__device__ __forceinline__ void sts64(uint32_t a, uint32_t x, uint32_t y) {
    asm volatile("st.shared.v2.u32 [%0], {%1,%2};" ::"r"(a), "r"(x), "r"(y) : "memory");
}
__device__ __forceinline__ void sts32(uint32_t a, uint32_t x) {
    asm volatile("st.volatile.shared.u32 [%0], %1;" ::"r"(a), "r"(x) : "memory");
}
__device__ __forceinline__ void poll128(uint4& v, const void* p, bool pred) {
    asm volatile("{\n .reg .pred p;\n setp.ne.u32 p, %5, 0;\n @p ld.relaxed.gpu.global.v4.u32 {%0,%1,%2,%3}, [%4];\n}"
                 : "+r"(v.x), "+r"(v.y), "+r"(v.z), "+r"(v.w) : "l"(p), "r"((uint32_t)pred) : "memory");
}
__device__ __forceinline__ void stg128(void* p, uint4 v) {
    asm volatile("st.relaxed.gpu.global.v4.u32 [%0], {%1,%2,%3,%4};" ::"l"(p), "r"(v.x), "r"(v.y), "r"(v.z), "r"(v.w) : "memory");
}
__device__ __forceinline__ void stg64(void* p, uint32_t x, uint32_t y) {
    asm volatile("st.relaxed.gpu.global.v2.u32 [%0], {%1,%2};" ::"l"(p), "r"(x), "r"(y) : "memory");
}
__device__ __forceinline__ void stg32(void* p, uint32_t x) {
    asm volatile("st.relaxed.gpu.global.u32 [%0], %1;" ::"l"(p), "r"(x) : "memory");
}
__device__ __forceinline__ uint32_t nz(float f) {
    uint32_t u = __float_as_uint(f);
    return u == 0u ? 0x80000000u : u;
}
__device__ __forceinline__ bool all_set(const uint4& v) { return v.x != 0u && v.y != 0u && v.z != 0u && v.w != 0u; }
__device__ __forceinline__ void poll2(uint4& a, const void* pa, uint4& b, const void* pb, int sleep_ns) {
    uint32_t n = 0;
    while (true) {
        const bool ma = !all_set(a), mb = !all_set(b);
        if (!__any_sync(0xffffffffu, ma || mb)) break;
        if (sleep_ns && n) __nanosleep(sleep_ns);
        poll128(a, pa, ma);
        poll128(b, pb, mb);
        if (++n > SPIN_LIMIT) __trap();
    }
}
__device__ __forceinline__ uint32_t pack_bf16(float lo, float hi) {
    uint32_t r;
    asm("cvt.rn.bf16x2.f32 %0, %1, %2;" : "=r"(r) : "f"(hi), "f"(lo));
    return r;
}
__device__ __forceinline__ float ex2(float x) {
    float r;
    asm("ex2.approx.ftz.f32 %0, %1;" : "=f"(r) : "f"(x));
    return r;
}
__device__ __forceinline__ float sel4(const float (&c)[4], int j) {
    float a = (j & 1) ? c[1] : c[0];
    float b = (j & 1) ? c[3] : c[2];
    return (j & 2) ? b : a;
}
__device__ __forceinline__ bool elect_one() {
    uint32_t p;
    asm volatile("{\n .reg .pred p;\n elect.sync _|p, 0xffffffff;\n selp.u32 %0, 1, 0, p;\n}" : "=r"(p));
    return p != 0;
}
__device__ __forceinline__ void bar_consumers() { asm volatile("bar.sync 1, 256;" ::: "memory"); }

__global__ void __launch_bounds__(NTHREADS, 1)
gqa2_decode_kernel(const __grid_constant__ Params prm) {
    extern __shared__ unsigned char smem_raw[];
    const uint32_t sb = ((uint32_t)__cvta_generic_to_shared(smem_raw) + 1023u) & ~1023u;
    const int tid = threadIdx.x, warp = tid >> 5, lane = tid & 31;
    const int bid = blockIdx.x, prob = bid >> 6, c = bid & 63;
    const uint32_t bar_full = sb + SM_BAR, bar_wo = bar_full + 16 * NST, bar_empty = bar_wo + 32;
    const uint32_t bar_ready = bar_empty + 8 * NST, bar_x = bar_ready + 8, bar_of = bar_ready + 16,
                   bar_go = bar_ready + 24, bar_ofa = bar_ready + 56;

    int wu = __shfl_sync(0xffffffffu, warp, 0);
    if (wu == 8) {
        uint64_t pol;
        asm volatile("createpolicy.fractional.L2::evict_first.b64 %0, 1.0;" : "=l"(pol));
        if (elect_one()) {
#pragma unroll
            for (int s = 0; s < 2 * NST; s++) mbar_init(bar_full + 8 * s, 1);
            asm volatile("fence.mbarrier_init.release.cluster;" ::: "memory");
#pragma unroll
            for (int n = 0; n < DEPTH; n++) {
                mbar_expect(bar_full + 8 * n, 12288);
                tma4d(sb + SM_RING + (n >> 1) * TILE + (n & 1) * 12288, &prm.tm[prob][0], c * 64, n * 96, 0, bar_full + 8 * n, pol);
            }
#pragma unroll
            for (int s = 0; s < 4; s++) mbar_init(bar_wo + 8 * s, 1);
#pragma unroll
            for (int s = 0; s < NST; s++) mbar_init(bar_empty + 8 * s, 8);
#pragma unroll
            for (int s = 0; s < 7; s++) mbar_init(bar_ready + 8 * s, s == 2 ? 2 : 1);
            mbar_init(bar_ofa, 6);
            asm volatile("fence.mbarrier_init.release.cluster;" ::: "memory");
            mbar_expect(bar_x, 1152);
            asm volatile("cp.async.bulk.shared::cluster.global.mbarrier::complete_tx::bytes [%0], [%1], 1152, [%2];"
                         ::"r"(sb + SM_X), "l"(prm.x[prob]), "r"(bar_x) : "memory");
            sts64(sb + SM_PROG, 0u, 0u);
#pragma unroll
            for (int k = 1; k < 4; k++) asm volatile("prefetch.tensormap [%0];" ::"l"(&prm.tm[prob][k]) : "memory");
        }
        __syncwarp();
        asm volatile("bar.arrive 3, %0;" ::"n"(NTHREADS) : "memory");
        int ib = DEPTH, iph = 0;
        int nw = 0, wb = 0, wph = 0;
#pragma unroll 1
        for (int n = DEPTH; n < 70; n++) {
            const bool kv = n >= 6;
            const int bytes = kv ? TILE / 2 : 12288;
            const uint32_t dst = sb + SM_RING + (ib >> 1) * TILE + (ib & 1) * bytes, bar = bar_full + 8 * ib;
            if (n >= 2 * NST && (n & 1) == 0) mbar_wait(bar_empty + 4 * ib, iph ^ 1);
            if (elect_one()) mbar_expect(bar, bytes);
            while (true) {
                int win = DEPTH;
                if (n >= 14) {
                    const int lag = (int)lds32v(sb + SM_PROG) - ((n - 10) * 128 - 256);
                    win = min(max(DEPTH + (lag >> 7), 2), 8);
                }
                if (n - nw < win) break;
                mbar_wait(bar_full + 8 * wb, wph);
                nw++;
                if (++wb == 2 * NST) { wb = 0; wph ^= 1; }
            }
            if (elect_one()) {
                tma4d(dst, &prm.tm[prob][kv + (n >= 38)], kv ? 0 : c * 64, kv ? 0 : n * 96, kv ? ((n - 6) & 31) * 512 + c * 8 : 0, bar, pol);
                if (n >= 10) sts32(sb + SM_PROG + 4, n - 9);
            }
            if (++ib == 2 * NST) { ib = 0; iph ^= 1; }
        }
#pragma unroll
        for (int k = 0; k < 4; k++) {
            if (k == 0) mbar_wait(bar_empty + 40, 0);
            else if (k < 3) mbar_wait(bar_empty + 8 * (k - 1), 1);
            for (int w = 6; w >= 2; w--) {
                const int m = 70 + k - w;
                mbar_wait(bar_full + 8 * (m < 70 ? m - 60 : m - 58), m < 70 ? 1 : 0);
                const int lag = (int)lds32v(sb + SM_PROG) - ((60 + k) * 128 - 256);
                if (w <= DEPTH + (lag >> 7)) break;
            }
            if (elect_one()) sts32(sb + SM_PROG + 4, 61 + k);
            if (elect_one())
                tma4d(sb + SM_RING + (k ? (k - 1) * 18432 : 5 * TILE), &prm.tm[prob][3], 0, (k * 1024 + (k < 3 ? (c ^ 48) : c) * 16) * 9, 0, bar_wo + 8 * k, pol);
        }
    } else {
        asm volatile("bar.sync 3, %0;" ::"n"(NTHREADS) : "memory");
    }
    asm volatile("" : "+r"(wu));
    const int g8 = lane >> 2, j4 = lane & 3, l8 = lane & 7, m4 = lane >> 3;
    const uint4 zero4 = make_uint4(0u, 0u, 0u, 0u);

    if (wu > 8) {
        if (wu < 11) {
            const int hf = wu - 9;
            float4* const psrc = g_s.part + bid * 1024 + hf * 128 + lane;
#pragma unroll
            for (int i = 0; i < 16; i++) { stg128(psrc + (i >> 2) * 256 + (i & 3) * 32, zero4); __nanosleep(300); }
            if (hf == 0) {
                const int e = c * 5 + lane;
                if (lane < 5) stg128(g_s.acc + (prob * 40 + (e >> 3)) * 72 + (e & 7), zero4);
            } else if (lane < 16) stg128(g_s.stat + bid * 16 + lane, zero4);
            asm volatile("bar.sync 2, 64;" ::: "memory");
            if (tid == 288) {
                unsigned int v, n = 0;
                asm volatile("atom.release.gpu.global.add.u32 %0, [%1], 1;" : "=r"(v) : "l"(g_s.cnt + prob * 32) : "memory");
                const unsigned int target = (v & ~63u) + 64u;
                do {
                    __nanosleep(n ? 1000 : 3000);
                    asm volatile("ld.relaxed.gpu.global.u32 %0, [%1];" : "=r"(v) : "l"(g_s.cnt + prob * 32) : "memory");
                    if (++n > SPIN_LIMIT) __trap();
                } while ((int)(v - target) < 0);
                asm volatile("ld.acquire.gpu.global.u32 %0, [%1];" : "=r"(v) : "l"(g_s.cnt + prob * 32) : "memory");
                mbar_arrive(bar_ready);
            }
            __syncwarp();
            mbar_wait(bar_go, 0);
            float e[4];
            {
                uint4 sa = zero4, sb2 = zero4, sc = zero4, sd = zero4;
                const float4* ssrc = g_s.stat + ((prob * 2 + ((c >> 3) & 1)) * 16 + 4 * m4 + (m4 < 3 ? 3 - (c >> 4) : (c >> 4))) * 32 + l8;
                poll128(sc, ssrc + 16 * (1 - hf), true);
                poll128(sd, ssrc + 16 * (1 - hf) + 8, true);
                poll2(sa, ssrc + 16 * hf, sb2, ssrc + 16 * hf + 8, 300);
                poll2(sc, ssrc + 16 * (1 - hf), sd, ssrc + 16 * (1 - hf) + 8, 300);
                if (hf == 0 && lane < 8) stg128(g_s.q + bid * 8 + lane, zero4);
                float M = fmaxf(fmaxf(fmaxf(__uint_as_float(sa.x), __uint_as_float(sa.z)), fmaxf(__uint_as_float(sb2.x), __uint_as_float(sb2.z))),
                                fmaxf(fmaxf(__uint_as_float(sc.x), __uint_as_float(sc.z)), fmaxf(__uint_as_float(sd.x), __uint_as_float(sd.z))));
#pragma unroll
                for (int o = 4; o > 0; o >>= 1) M = fmaxf(M, __shfl_xor_sync(0xffffffffu, M, o));
                e[0] = ex2(__uint_as_float(sa.x) - M); e[1] = ex2(__uint_as_float(sa.z) - M);
                e[2] = ex2(__uint_as_float(sb2.x) - M); e[3] = ex2(__uint_as_float(sb2.z) - M);
                const float La = (e[0] * __uint_as_float(sa.y) + e[1] * __uint_as_float(sa.w)) + (e[2] * __uint_as_float(sb2.y) + e[3] * __uint_as_float(sb2.w));
                const float Lb = (ex2(__uint_as_float(sc.x) - M) * __uint_as_float(sc.y) + ex2(__uint_as_float(sc.z) - M) * __uint_as_float(sc.w)) +
                                 (ex2(__uint_as_float(sd.x) - M) * __uint_as_float(sd.y) + ex2(__uint_as_float(sd.z) - M) * __uint_as_float(sd.w));
                float L = La + Lb;
#pragma unroll
                for (int o = 4; o > 0; o >>= 1) L += __shfl_xor_sync(0xffffffffu, L, o);
                const float inv = 1.0f / L;
#pragma unroll
                for (int i = 0; i < 4; i++) e[i] *= inv;
            }
            const bool up = lane >= 16;
            const int pr = 2 * j4 + (up ? 1 : 0);
            const uint32_t of_addr = sb + SM_OF + hf * 128 + ((pr & 3) * 8 + (pr >> 2)) * 4;
#pragma unroll 1
            for (int t = 0; t < 4; t++) {
                float wg[4];
#pragma unroll
                for (int i = 0; i < 4; i++) {
                    const float u0 = __shfl_sync(0xffffffffu, e[i & 2], 8 * t + 4 * (i & 1) + (g8 >> 1));
                    const float u1 = __shfl_sync(0xffffffffu, e[(i & 2) + 1], 8 * t + 4 * (i & 1) + (g8 >> 1));
                    wg[i] = (g8 & 1) ? u1 : u0;
                }
                mbar_wait(bar_go + 8 * t, 0);
                uint4 pv[4] = {zero4, zero4, zero4, zero4};
                {
                    uint32_t n = 0;
                    while (true) {
                        bool m[4], miss = false;
#pragma unroll
                        for (int i = 0; i < 4; i++) { m[i] = !all_set(pv[i]); miss |= m[i]; }
                        if (!__any_sync(0xffffffffu, miss)) break;
                        if (t < 3 && n) __nanosleep(300);
#pragma unroll
                        for (int i = 0; i < 4; i++) poll128(pv[i], psrc + 256 * t + 32 * i, m[i]);
                        if (++n > SPIN_LIMIT) __trap();
                    }
                }
                const float x = (wg[0] * __uint_as_float(pv[0].x) + wg[1] * __uint_as_float(pv[1].x)) + (wg[2] * __uint_as_float(pv[2].x) + wg[3] * __uint_as_float(pv[3].x));
                const float y = (wg[0] * __uint_as_float(pv[0].y) + wg[1] * __uint_as_float(pv[1].y)) + (wg[2] * __uint_as_float(pv[2].y) + wg[3] * __uint_as_float(pv[3].y));
                const float z = (wg[0] * __uint_as_float(pv[0].z) + wg[1] * __uint_as_float(pv[1].z)) + (wg[2] * __uint_as_float(pv[2].z) + wg[3] * __uint_as_float(pv[3].z));
                const float w = (wg[0] * __uint_as_float(pv[0].w) + wg[1] * __uint_as_float(pv[1].w)) + (wg[2] * __uint_as_float(pv[2].w) + wg[3] * __uint_as_float(pv[3].w));
                float k0 = (up ? z : x) + __shfl_xor_sync(0xffffffffu, up ? x : z, 16);
                float k1 = (up ? w : y) + __shfl_xor_sync(0xffffffffu, up ? y : w, 16);
#pragma unroll
                for (int o = 8; o > 2; o >>= 1) {
                    k0 += __shfl_xor_sync(0xffffffffu, k0, o);
                    k1 += __shfl_xor_sync(0xffffffffu, k1, o);
                }
                if ((lane & 12) == 0) sts32(of_addr + 8 * t, pack_bf16(k0, k1));
                __syncwarp();
                if (lane == 0) mbar_arrive(t < 3 ? bar_ofa : bar_of);
            }
        } else {
            if (lane < 4) mbar_expect(bar_wo + 8 * lane, 18432);
            if (lane == 0) {
                uint32_t rep = 0, n = 0;
                while (rep < 64u) {
                    const uint32_t cur = lds32v(sb + SM_PROG + 4);
                    if (cur == rep) { __nanosleep(40); if (++n > (SPIN_LIMIT << 2)) __trap(); continue; }
                    uint32_t v;
                    asm volatile("atom.relaxed.gpu.global.add.u32 %0, [%1], %2;" : "=r"(v) : "l"(g_s.cnt + 64), "r"(cur - rep) : "memory");
                    sts32(sb + SM_PROG, v);
                    if (v + (cur - rep) == 128u * 64u) stg32(g_s.cnt + 64, 0u);
                    rep = cur;
                }
            }
        }
        return;
    } else if (wu < 8) {
        {
            uint32_t xb[3][12];
            mbar_wait(bar_x, 0);
#pragma unroll
            for (int b = 0; b < 3; b++)
#pragma unroll
                for (int t = 0; t < 12; t++) xb[b][t] = lds32v(sb + SM_X + ((warp >> 2) * 48 + j4 + b * 96 + 4 * t) * 4);
            float c0[4] = {0.f, 0.f, 0.f, 0.f}, c1[4] = {0.f, 0.f, 0.f, 0.f};
            const uint32_t base = sb + SM_RING + ((warp >> 2) * 96 + (m4 >> 1) * 8 + l8) * 128 + (((2 * (warp & 3) + (m4 & 1)) ^ l8) << 4);
#pragma unroll
            for (int b = 0; b < 3; b++) {
                mbar_wait(bar_full + 16 * b + 8 * (warp >> 2), 0);
#pragma unroll
                for (int t = 0; t < 3; t++) {
                    uint32_t a0[4], a1[4];
                    ldsm4t(a0, base + b * TILE + (2 * t) * 2048);
                    ldsm4t(a1, base + b * TILE + (2 * t + 1) * 2048);
                    mma16816(c0, a0, xb[b][4 * t], xb[b][4 * t + 1]);
                    mma16816(c1, a1, xb[b][4 * t + 2], xb[b][4 * t + 3]);
                }
                __syncwarp();
                if (lane == 0) mbar_arrive(bar_empty + 8 * b);
            }
            if (j4 < 2) sts32(sb + SM_RED + (warp * 16 + g8 + 8 * j4) * 4, __float_as_uint(j4 ? c0[2] + c1[2] : c0[0] + c1[0]));
        }
        bar_consumers();
        if (warp == 0) {
            const float2 va = lds64f(sb + SM_RED + lane * 8), vb = lds64f(sb + SM_RED + 256 + lane * 8);
            uint32_t u = pack_bf16(va.x + vb.x, va.y + vb.y);
            if (u == 0u) u = 0x8000u;
            const int d = 64 * (c & 1) + 2 * lane;
            const int w16 = 2 * (d >> 4) + ((d >> 3) & 1);
            stg32(reinterpret_cast<uint32_t*>(g_s.q) + (bid >> 2) * 128 + (w16 >> 2) * 32 + ((c >> 1) & 1) * 16 + ((d & 7) >> 1) * 4 + (w16 & 3), u);
        }
        {
            uint4 v = zero4, v2 = zero4;
            mbar_wait(bar_full + 8 * 9, 0);
            poll2(v, g_s.q + prob * 512 + tid, v2, g_s.q + prob * 512 + 256 + tid, 300);
            sts128(sb + SM_Q + tid * 16, v);
            sts128(sb + SM_Q + 4096 + tid * 16, v2);
        }
        bar_consumers();
        const uint32_t frag_off = (g8 & 1) * 64 + j4 * 16;
        int s = 3, ph = 0;

        {
            const uint32_t kbase = sb + SM_RING + (2 * warp + (m4 & 1)) * 2048 + l8 * 128 + (((m4 >> 1) ^ l8) << 4);
            const uint32_t sc_addr = sb + SM_SC + (warp * 32 + (j4 & 1) * 16 + (g8 >> 1) * 4 + (g8 & 1) + (j4 >> 1) * 2) * 4;
#pragma unroll 1
            for (int i = 0; i < 16; i++) {
                uint4 qb[4];
#pragma unroll
                for (int q = 0; q < 4; q++) qb[q] = lds128(sb + SM_Q + i * 512 + q * 128 + frag_off);
                mbar_wait(bar_full + 16 * s + 8 * (warp >> 2), ph);
                float c0[4] = {0.f, 0.f, 0.f, 0.f}, c1[4] = {0.f, 0.f, 0.f, 0.f};
                const uint32_t kb = kbase + s * TILE;
#pragma unroll
                for (int q = 0; q < 4; q++) {
                    uint32_t a0[4], a1[4];
                    ldsm4(a0, (kb ^ (((2 * q) & 3) << 5)) + (q >> 1) * 1024);
                    ldsm4(a1, (kb ^ (((2 * q + 1) & 3) << 5)) + (q >> 1) * 1024);
                    mma16816(c0, a0, qb[q].x, qb[q].y);
                    mma16816(c1, a1, qb[q].z, qb[q].w);
                }
                __syncwarp();
                if (lane == 0) mbar_arrive(bar_empty + 8 * s);
                sts32(sc_addr + i * 1024, __float_as_uint(sel4(c0, j4) + sel4(c1, j4)));
                if (++s == NST) { s = 0; ph ^= 1; }
            }
        }
        mbar_wait(bar_ready, 0);
        bar_consumers();

        {
            constexpr float SCALE = 0.08838834764831845f * 1.4426950408889634f;
            const int hd = warp & 1, st = warp >> 1;
            float4 sv[4];
            float ms[4], sum[4];
#pragma unroll
            for (int t = 0; t < 4; t++) {
                sv[t] = lds128f(sb + SM_SC + ((4 * st + t) * 256 + g8 * 32 + hd * 16 + j4 * 4) * 4);
                ms[t] = fmaxf(fmaxf(sv[t].x, sv[t].y), fmaxf(sv[t].z, sv[t].w));
            }
#pragma unroll
            for (int o = 16; o > 0; o >>= 1)
#pragma unroll
                for (int t = 0; t < 4; t++) ms[t] = fmaxf(ms[t], __shfl_xor_sync(0xffffffffu, ms[t], o));
#pragma unroll
            for (int t = 0; t < 4; t++) {
                ms[t] *= SCALE;
                const float m = ms[t];
                const float p0 = ex2(fmaf(sv[t].x, SCALE, -m)), p1 = ex2(fmaf(sv[t].y, SCALE, -m));
                const float p2 = ex2(fmaf(sv[t].z, SCALE, -m)), p3 = ex2(fmaf(sv[t].w, SCALE, -m));
                sum[t] = (p0 + p1) + (p2 + p3);
                sts64(sb + SM_P + (4 * st + t) * 512 + (g8 >> 1) * 128 + hd * 64 + j4 * 16 + (g8 & 1) * 8, pack_bf16(p0, p1), pack_bf16(p2, p3));
            }
            bar_consumers();
#pragma unroll
            for (int o = 16; o > 0; o >>= 1)
#pragma unroll
                for (int t = 0; t < 4; t++) sum[t] += __shfl_xor_sync(0xffffffffu, sum[t], o);
            if (lane < 4)
                stg64(reinterpret_cast<float2*>(g_s.stat) + ((prob * 2 + hd) * 16 + 4 * st + lane) * 64 + c, nz(sel4(ms, lane)), nz(sel4(sum, lane)));
        }

        {
            const uint32_t vbase = sb + SM_RING + (m4 >> 1) * 2048 + (warp >> 2) * 1024 + l8 * 128 + (((2 * (warp & 3) + (m4 & 1)) ^ l8) << 4);
            float* const dst = reinterpret_cast<float*>(g_s.part) + (prob * 64 + 8 * (j4 & 1) + warp) * 4096 + c * 16 + g8 + 8 * (j4 >> 1);
            const int go_off = 6 - (c >> 4);
#pragma unroll 1
            for (int i = 0; i < 16; i++) {
                float c0[4] = {0.f, 0.f, 0.f, 0.f}, c1[4] = {0.f, 0.f, 0.f, 0.f};
                uint4 pb[4];
#pragma unroll
                for (int q = 0; q < 4; q++) pb[q] = lds128(sb + SM_P + i * 512 + q * 128 + frag_off);
                const uint32_t vb = vbase + s * TILE;
#pragma unroll
                for (int q = 0; q < 4; q++) {
                    uint32_t a0[4], a1[4];
                    if ((q & 1) == 0) mbar_wait(bar_full + 16 * s + 4 * q, ph);
                    ldsm4t(a0, vb + (2 * q) * 4096);
                    ldsm4t(a1, vb + (2 * q + 1) * 4096);
                    mma16816(c0, a0, pb[q].x, pb[q].y);
                    mma16816(c1, a1, pb[q].z, pb[q].w);
                }
                __syncwarp();
                if (lane == 0) mbar_arrive(bar_empty + 8 * s);
                stg32(dst + (i < 12 ? 3 - (i & 3) : (i & 3)) * (16 * 4096) + (i >> 2) * 1024, nz(sel4(c0, j4) + sel4(c1, j4)));
                if (tid == 0 && (i == 15 || (i >= go_off && ((i - go_off) & 3) == 0)))
                    mbar_arrive(bar_go + (i == 15 ? 24 : 2 * (i - go_off)));
                if (++s == NST) { s = 0; ph ^= 1; }
            }
        }
    }

    {
        float acc[2][4][4];
#pragma unroll
        for (int e = 0; e < 32; e++) (&acc[0][0][0])[e] = 0.f;
        const int rho = 9 * ((m4 >> 1) * 8 + l8) + warp;
        uint32_t base[4];
#pragma unroll
        for (int mt = 0; mt < 4; mt++) base[mt] = (sb + SM_RING + rho * 128 + (((m4 & 1) ^ (rho & 7)) << 4)) ^ (mt << 5);
        float4* dst = g_s.acc + (prob * 40 + (tid >> 3)) * 72 + (tid & 7);
        __nv_bfloat16* optr = prm.out + prob * 576 + warp * 64 + 16 * j4 + g8;
        uint32_t js = j4, of_addr = sb + SM_OF + (g8 & 1) * 128 + j4 * 32;
        asm volatile("" : "+r"(base[0]), "+r"(base[1]), "+r"(base[2]), "+r"(base[3]), "+l"(dst), "+l"(optr), "+r"(js), "+r"(of_addr));
        uint32_t wa[2][4][4];
#define LOAD_W(t) _Pragma("unroll") for (int mt = 0; mt < 4; mt++) ldsm4t(wa[(t) & 1][mt], base[mt] + ((t) ? ((t) - 1) * 18432 : 5 * TILE))
#define MMA_W(t, b0, b1) _Pragma("unroll") for (int mt = 0; mt < 4; mt++) mma16816(acc[(t) & 1][mt], wa[(t) & 1][mt], b0, b1)
        auto pick = [&](int a, int e) {
            float r;
            asm("{\n .reg .pred p, q;\n .reg .f32 u, v;\n .reg .b32 t;\n and.b32 t, %5, 1;\n setp.ne.u32 p, t, 0;\n setp.gt.u32 q, %5, 1;\n"
                " selp.f32 u, %2, %1, p;\n selp.f32 v, %4, %3, p;\n selp.f32 %0, v, u, q;\n}"
                : "=f"(r) : "f"(acc[a][0][e]), "f"(acc[a][1][e]), "f"(acc[a][2][e]), "f"(acc[a][3][e]), "r"(js));
            return r;
        };
        mbar_wait(bar_ofa, 0);
        const uint4 o0 = lds128(of_addr);
        const float2 o1 = lds64f(of_addr + 16);
        mbar_wait(bar_wo, 0);
        LOAD_W(0);
        MMA_W(0, o0.x, o0.y);
        mbar_wait(bar_wo + 8, 0);
        LOAD_W(1);
        MMA_W(1, o0.z, o0.w);
        mbar_wait(bar_wo + 16, 0);
        LOAD_W(2);
        const bool have_w = mbar_test(bar_wo + 24, 0);
        if (have_w) { LOAD_W(3); }
        MMA_W(2, __float_as_uint(o1.x), __float_as_uint(o1.y));
        float2 o2;
        bool have_o = false;
        if (!have_w) {
            uint32_t n = 0;
            while (!mbar_test(bar_wo + 24, 0)) {
                if (mbar_test(bar_of, 0)) {
                    o2 = lds64f(of_addr + 24);
                    have_o = true;
                    mbar_wait(bar_wo + 24, 0);
                    break;
                }
                if (++n > (SPIN_LIMIT << 4)) __trap();
            }
            LOAD_W(3);
        }
        if (!have_o) { mbar_wait(bar_of, 0); o2 = lds64f(of_addr + 24); }
        MMA_W(3, __float_as_uint(o2.x), __float_as_uint(o2.y));
        const float v0 = (pick(0, 0) + pick(0, 1)) + (pick(1, 0) + pick(1, 1)), v1 = (pick(0, 2) + pick(0, 3)) + (pick(1, 2) + pick(1, 3));
        float r0, r1, r2;
        asm volatile("{\n .reg .f32 t;\n atom.relaxed.gpu.global.add.v4.f32 {%0,%1,%2,t}, [%3], {%4,%5,%6,%7};\n}"
                     : "=f"(r0), "=f"(r1), "=f"(r2) : "l"(dst), "f"(v0), "f"(v1), "f"(1.0f), "f"(0.0f) : "memory");
        if (r2 == 63.0f) { optr[0] = __float2bfloat16(r0 + v0); optr[8] = __float2bfloat16(r1 + v1); }
#undef LOAD_W
#undef MMA_W
    }
}

typedef CUresult (*EncodeFn)(CUtensorMap*, CUtensorMapDataType, cuuint32_t, void*, const cuuint64_t*, const cuuint64_t*,
                             const cuuint32_t*, const cuuint32_t*, CUtensorMapInterleave, CUtensorMapSwizzle,
                             CUtensorMapL2promotion, CUtensorMapFloatOOBfill);

}

extern "C" void kernel_launch(void* const* d_in, const int* in_sizes, int n_in, void* d_out, int out_size) {
    (void)in_sizes; (void)n_in; (void)out_size;
    static EncodeFn enc = nullptr;
    if (!enc) {
        cudaDriverEntryPointQueryResult qr;
        void* fn = nullptr;
        cudaGetDriverEntryPoint("cuTensorMapEncodeTiled", &fn, cudaEnableDefault, &qr);
        enc = (EncodeFn)fn;
        cudaFuncSetAttribute(gqa2_decode_kernel, cudaFuncAttributeMaxDynamicSharedMemorySize, SM_TOTAL);
    }
    Params prm;
    const cuuint32_t es[4] = {1, 1, 1, 1};
    for (int p = 0; p < 2; p++) {
        prm.x[p] = (const __nv_bfloat16*)d_in[5 * p + 0];
        void* ptr[4] = {d_in[5 * p + 3], d_in[5 * p + 1], d_in[5 * p + 2], d_in[5 * p + 4]};
        const cuuint64_t gd[4][4] = {{4096, 576, 1, 1}, {64, 8, 2, 16 * 8192 / 8}, {64, 8, 2, 16 * 8192 / 8}, {64, 4096 * 9, 1, 1}};
        const cuuint64_t gs[4][3] = {{8192, 8192 * 576, 8192 * 576}, {256, 128, 2048}, {256, 128, 2048}, {128, 128 * 4096 * 9, 128 * 4096 * 9}};
        const cuuint32_t bd[4][4] = {{64, 96, 1, 1}, {64, 8, 2, 8}, {64, 8, 2, 8}, {64, 144, 1, 1}};
        for (int i = 0; i < 4; i++)
            enc(&prm.tm[p][i], CU_TENSOR_MAP_DATA_TYPE_BFLOAT16, 4, ptr[i], gd[i], gs[i], bd[i], es,
                CU_TENSOR_MAP_INTERLEAVE_NONE, CU_TENSOR_MAP_SWIZZLE_128B, CU_TENSOR_MAP_L2_PROMOTION_L2_128B,
                CU_TENSOR_MAP_FLOAT_OOB_FILL_NONE);
    }
    prm.out = (__nv_bfloat16*)d_out;
    gqa2_decode_kernel<<<128, NTHREADS, SM_TOTAL>>>(prm);
}
```

```cpp
#include <cuda_runtime.h>
#include <cuda_bf16.h>
#include <cuda.h>
#include <stdint.h>

namespace {

constexpr int TILE = 32768;
constexpr int NST  = 6;
constexpr int DEPTH = 4;
constexpr int NTHREADS = 384;

constexpr int SM_RING = 0;
constexpr int SM_SC   = NST * TILE;
constexpr int SM_P    = SM_SC + 16384;
constexpr int SM_Q    = SM_P;
constexpr int SM_X    = SM_P + 8192;
constexpr int SM_RED  = SM_X + 1152;
constexpr int SM_OF   = SM_RED + 512;
constexpr int SM_PROG = SM_OF + 256;
constexpr int SM_BAR  = SM_PROG + 16;
constexpr int SM_TOTAL = SM_BAR + 256;

struct alignas(64) Params {
    CUtensorMap tm[2][4];
    const __nv_bfloat16* x[2];
    __nv_bfloat16* out;
};

struct alignas(4096) Scratch {
    float4 acc[4 * 40 * 72];
    float4 part[128 * 1024];
    uint4  q[128 * 8];
    float4 stat[128 * 16];
    unsigned int cnt[3 * 32];
};
__device__ Scratch g_s;

constexpr uint32_t SPIN_LIMIT = 1u << 22;

__device__ __forceinline__ void mbar_init(uint32_t a, uint32_t c) {
    asm volatile("mbarrier.init.shared::cta.b64 [%0], %1;" ::"r"(a), "r"(c) : "memory");
}
__device__ __forceinline__ void mbar_expect(uint32_t a, uint32_t b) {
    asm volatile("mbarrier.arrive.expect_tx.shared::cta.b64 _, [%0], %1;" ::"r"(a), "r"(b) : "memory");
}
__device__ __forceinline__ void mbar_arrive(uint32_t a) {
    asm volatile("mbarrier.arrive.shared::cta.b64 _, [%0];" ::"r"(a) : "memory");
}
__device__ __forceinline__ void mbar_wait(uint32_t a, uint32_t ph) {
    uint32_t ok, n = 0;
    do {
        asm volatile("{\n .reg .pred p;\n mbarrier.try_wait.parity.shared::cta.b64 p, [%1], %2;\n selp.u32 %0, 1, 0, p;\n}"
                     : "=r"(ok) : "r"(a), "r"(ph) : "memory");
        if (++n > SPIN_LIMIT) __trap();
    } while (!ok);
}
__device__ __forceinline__ bool mbar_test(uint32_t a, uint32_t ph) {
    uint32_t ok;
    asm volatile("{\n .reg .pred p;\n mbarrier.test_wait.parity.shared::cta.b64 p, [%1], %2;\n selp.u32 %0, 1, 0, p;\n}"
                 : "=r"(ok) : "r"(a), "r"(ph) : "memory");
    return __all_sync(0xffffffffu, ok != 0);
}
__device__ __forceinline__ void tma4d(uint32_t dst, const CUtensorMap* tm, int c0, int c1, int c3, uint32_t mbar, uint64_t pol) {
    asm volatile("cp.async.bulk.tensor.4d.shared::cluster.global.mbarrier::complete_tx::bytes.L2::cache_hint"
                 " [%0], [%1, {%3, %4, %5, %6}], [%2], %7;"
                 ::"r"(dst), "l"(tm), "r"(mbar), "r"(c0), "r"(c1), "r"(0), "r"(c3), "l"(pol) : "memory");
}
__device__ __forceinline__ void ldsm4(uint32_t (&r)[4], uint32_t a) {
    asm volatile("ldmatrix.sync.aligned.m8n8.x4.shared.b16 {%0,%1,%2,%3}, [%4];"
                 : "=r"(r[0]), "=r"(r[1]), "=r"(r[2]), "=r"(r[3]) : "r"(a) : "memory");
}
__device__ __forceinline__ void ldsm4t(uint32_t (&r)[4], uint32_t a) {
    asm volatile("ldmatrix.sync.aligned.m8n8.x4.trans.shared.b16 {%0,%1,%2,%3}, [%4];"
                 : "=r"(r[0]), "=r"(r[1]), "=r"(r[2]), "=r"(r[3]) : "r"(a) : "memory");
}
__device__ __forceinline__ void mma16816(float (&c)[4], const uint32_t (&a)[4], uint32_t b0, uint32_t b1) {
    asm volatile("mma.sync.aligned.m16n8k16.row.col.f32.bf16.bf16.f32 {%0,%1,%2,%3}, {%4,%5,%6,%7}, {%8,%9}, {%0,%1,%2,%3};"
                 : "+f"(c[0]), "+f"(c[1]), "+f"(c[2]), "+f"(c[3])
                 : "r"(a[0]), "r"(a[1]), "r"(a[2]), "r"(a[3]), "r"(b0), "r"(b1));
}
__device__ __forceinline__ uint4 lds128(uint32_t a) {
    uint4 v;
    asm volatile("ld.shared.v4.u32 {%0,%1,%2,%3}, [%4];" : "=r"(v.x), "=r"(v.y), "=r"(v.z), "=r"(v.w) : "r"(a) : "memory");
    return v;
}
__device__ __forceinline__ float4 lds128f(uint32_t a) {
    float4 v;
    asm volatile("ld.shared.v4.f32 {%0,%1,%2,%3}, [%4];" : "=f"(v.x), "=f"(v.y), "=f"(v.z), "=f"(v.w) : "r"(a) : "memory");
    return v;
}
__device__ __forceinline__ float2 lds64f(uint32_t a) {
    float2 v;
    asm volatile("ld.shared.v2.f32 {%0,%1}, [%2];" : "=f"(v.x), "=f"(v.y) : "r"(a) : "memory");
    return v;
}
__device__ __forceinline__ uint32_t lds32v(uint32_t a) {
    uint32_t v;
    asm volatile("ld.volatile.shared.u32 %0, [%1];" : "=r"(v) : "r"(a) : "memory");
    return v;
}
__device__ __forceinline__ void sts128(uint32_t a, uint4 v) {
    asm volatile("st.shared.v4.u32 [%0], {%1,%2,%3,%4};" ::"r"(a), "r"(v.x), "r"(v.y), "r"(v.z), "r"(v.w) : "memory");
}
__device__ __forceinline__ void sts64(uint32_t a, uint32_t x, uint32_t y) {
    asm volatile("st.shared.v2.u32 [%0], {%1,%2};" ::"r"(a), "r"(x), "r"(y) : "memory");
}
__device__ __forceinline__ void sts32(uint32_t a, uint32_t x) {
    asm volatile("st.volatile.shared.u32 [%0], %1;" ::"r"(a), "r"(x) : "memory");
}
__device__ __forceinline__ void poll128(uint4& v, const void* p, bool pred) {
    asm volatile("{\n .reg .pred p;\n setp.ne.u32 p, %5, 0;\n @p ld.relaxed.gpu.global.v4.u32 {%0,%1,%2,%3}, [%4];\n}"
                 : "+r"(v.x), "+r"(v.y), "+r"(v.z), "+r"(v.w) : "l"(p), "r"((uint32_t)pred) : "memory");
}
__device__ __forceinline__ void stg128(void* p, uint4 v) {
    asm volatile("st.relaxed.gpu.global.v4.u32 [%0], {%1,%2,%3,%4};" ::"l"(p), "r"(v.x), "r"(v.y), "r"(v.z), "r"(v.w) : "memory");
}
__device__ __forceinline__ void stg64(void* p, uint32_t x, uint32_t y) {
    asm volatile("st.relaxed.gpu.global.v2.u32 [%0], {%1,%2};" ::"l"(p), "r"(x), "r"(y) : "memory");
}
__device__ __forceinline__ void stg32(void* p, uint32_t x) {
    asm volatile("st.relaxed.gpu.global.u32 [%0], %1;" ::"l"(p), "r"(x) : "memory");
}
__device__ __forceinline__ uint32_t nz(float f) {
    uint32_t u = __float_as_uint(f);
    return u == 0u ? 0x80000000u : u;
}
__device__ __forceinline__ bool all_set(const uint4& v) { return v.x != 0u && v.y != 0u && v.z != 0u && v.w != 0u; }
__device__ __forceinline__ void poll2(uint4& a, const void* pa, uint4& b, const void* pb, int sleep_ns) {
    uint32_t n = 0;
    while (true) {
        const bool ma = !all_set(a), mb = !all_set(b);
        if (!__any_sync(0xffffffffu, ma || mb)) break;
        if (sleep_ns && n) __nanosleep(sleep_ns);
        poll128(a, pa, ma);
        poll128(b, pb, mb);
        if (++n > SPIN_LIMIT) __trap();
    }
}
__device__ __forceinline__ uint32_t pack_bf16(float lo, float hi) {
    uint32_t r;
    asm("cvt.rn.bf16x2.f32 %0, %1, %2;" : "=r"(r) : "f"(hi), "f"(lo));
    return r;
}
__device__ __forceinline__ float ex2(float x) {
    float r;
    asm("ex2.approx.ftz.f32 %0, %1;" : "=f"(r) : "f"(x));
    return r;
}
__device__ __forceinline__ float sel4(const float (&c)[4], int j) {
    float a = (j & 1) ? c[1] : c[0];
    float b = (j & 1) ? c[3] : c[2];
    return (j & 2) ? b : a;
}
__device__ __forceinline__ bool elect_one() {
    uint32_t p;
    asm volatile("{\n .reg .pred p;\n elect.sync _|p, 0xffffffff;\n selp.u32 %0, 1, 0, p;\n}" : "=r"(p));
    return p != 0;
}
__device__ __forceinline__ void bar_consumers() { asm volatile("bar.sync 1, 256;" ::: "memory"); }

__global__ void __launch_bounds__(NTHREADS, 1)
gqa2_decode_kernel(const __grid_constant__ Params prm) {
    extern __shared__ __align__(1024) unsigned char smem_raw[];
    constexpr uint32_t sb = 1024;
    const int tid = threadIdx.x, warp = tid >> 5, lane = tid & 31;
    const int bid = blockIdx.x, prob = bid >> 6, c = bid & 63;
    const uint32_t bar_full = sb + SM_BAR, bar_wo = bar_full + 16 * NST, bar_empty = bar_wo + 32;
    const uint32_t bar_ready = bar_empty + 8 * NST, bar_x = bar_ready + 8, bar_of = bar_ready + 16,
                   bar_go = bar_ready + 24, bar_ofa = bar_ready + 56;

    int wu = __shfl_sync(0xffffffffu, warp, 0);
    if (wu == 8) {
        uint64_t pol;
        asm volatile("createpolicy.fractional.L2::evict_first.b64 %0, 1.0;" : "=l"(pol));
        if (elect_one()) {
            mbar_init(bar_full, 1);
            asm volatile("fence.mbarrier_init.release.cluster;" ::: "memory");
            mbar_expect(bar_full, 12288);
            tma4d(sb + SM_RING, &prm.tm[prob][0], c * 64, 0, 0, bar_full, pol);
        }
        __syncwarp();
        if (elect_one()) {
#pragma unroll
            for (int s = 1; s < DEPTH; s++) mbar_init(bar_full + 8 * s, 1);
            asm volatile("fence.mbarrier_init.release.cluster;" ::: "memory");
#pragma unroll
            for (int n = 1; n < DEPTH; n++) {
                mbar_expect(bar_full + 8 * n, 12288);
                tma4d(sb + SM_RING + (n >> 1) * TILE + (n & 1) * 12288, &prm.tm[prob][0], c * 64, n * 96, 0, bar_full + 8 * n, pol);
            }
        }
        __syncwarp();
        if (elect_one()) {
            if ((uint32_t)__cvta_generic_to_shared(smem_raw) != sb) __trap();
#pragma unroll
            for (int s = DEPTH; s < 2 * NST; s++) mbar_init(bar_full + 8 * s, 1);
#pragma unroll
            for (int s = 0; s < 4; s++) mbar_init(bar_wo + 8 * s, 1);
#pragma unroll
            for (int s = 0; s < NST; s++) mbar_init(bar_empty + 8 * s, 8);
#pragma unroll
            for (int s = 0; s < 7; s++) mbar_init(bar_ready + 8 * s, s == 2 ? 2 : 1);
            mbar_init(bar_ofa, 6);
            asm volatile("fence.mbarrier_init.release.cluster;" ::: "memory");
            mbar_expect(bar_x, 1152);
            asm volatile("cp.async.bulk.shared::cluster.global.mbarrier::complete_tx::bytes [%0], [%1], 1152, [%2];"
                         ::"r"(sb + SM_X), "l"(prm.x[prob]), "r"(bar_x) : "memory");
            sts64(sb + SM_PROG, 0u, 0u);
#pragma unroll
            for (int k = 1; k < 4; k++) asm volatile("prefetch.tensormap [%0];" ::"l"(&prm.tm[prob][k]) : "memory");
        }
        __syncwarp();
        asm volatile("bar.arrive 3, %0;" ::"n"(NTHREADS) : "memory");
        int ib = DEPTH, iph = 0;
        int nw = 0, wb = 0, wph = 0;
#pragma unroll 1
        for (int n = DEPTH; n < 70; n++) {
            const bool kv = n >= 6;
            const int bytes = kv ? TILE / 2 : 12288;
            const uint32_t dst = sb + SM_RING + (ib >> 1) * TILE + (ib & 1) * bytes, bar = bar_full + 8 * ib;
            if (n >= 2 * NST && (n & 1) == 0) mbar_wait(bar_empty + 4 * ib, iph ^ 1);
            if (elect_one()) mbar_expect(bar, bytes);
            while (true) {
                int win = DEPTH;
                if (n >= 14) {
                    const int lag = (int)lds32v(sb + SM_PROG) - ((n - 10) * 128 - 256);
                    win = min(max(DEPTH + (lag >> 7), 2), 8);
                }
                if (n - nw < win) break;
                mbar_wait(bar_full + 8 * wb, wph);
                nw++;
                if (++wb == 2 * NST) { wb = 0; wph ^= 1; }
            }
            if (elect_one()) {
                tma4d(dst, &prm.tm[prob][kv + (n >= 38)], kv ? 0 : c * 64, kv ? 0 : n * 96, kv ? ((n - 6) & 31) * 512 + c * 8 : 0, bar, pol);
                if (n >= 10) sts32(sb + SM_PROG + 4, n - 9);
            }
            if (++ib == 2 * NST) { ib = 0; iph ^= 1; }
        }
#pragma unroll
        for (int k = 0; k < 4; k++) {
            if (k == 0) mbar_wait(bar_empty + 40, 0);
            else if (k < 3) mbar_wait(bar_empty + 8 * (k - 1), 1);
            for (int w = 6; w >= 2; w--) {
                const int m = 70 + k - w;
                mbar_wait(bar_full + 8 * (m < 70 ? m - 60 : m - 58), m < 70 ? 1 : 0);
                const int lag = (int)lds32v(sb + SM_PROG) - ((60 + k) * 128 - 256);
                if (w <= DEPTH + (lag >> 7)) break;
            }
            if (elect_one()) sts32(sb + SM_PROG + 4, 61 + k);
            if (elect_one())
                tma4d(sb + SM_RING + (k ? (k - 1) * 18432 : 5 * TILE), &prm.tm[prob][3], 0, (k * 1024 + (k < 3 ? (c ^ 48) : c) * 16) * 9, 0, bar_wo + 8 * k, pol);
        }
    } else {
        asm volatile("bar.sync 3, %0;" ::"n"(NTHREADS) : "memory");
    }
    asm volatile("" : "+r"(wu));
    const int g8 = lane >> 2, j4 = lane & 3, l8 = lane & 7, m4 = lane >> 3;
    const uint4 zero4 = make_uint4(0u, 0u, 0u, 0u);

    if (wu > 8) {
        if (wu < 11) {
            const int hf = wu - 9;
            float4* const psrc = g_s.part + bid * 1024 + hf * 128 + lane;
#pragma unroll
            for (int i = 0; i < 16; i++) { stg128(psrc + (i >> 2) * 256 + (i & 3) * 32, zero4); __nanosleep(300); }
            if (hf == 0) {
                const int e = c * 5 + lane;
                if (lane < 5) stg128(g_s.acc + (prob * 40 + (e >> 3)) * 72 + (e & 7), zero4);
            } else if (lane < 16) stg128(g_s.stat + bid * 16 + lane, zero4);
            asm volatile("bar.sync 2, 64;" ::: "memory");
            if (tid == 288) {
                unsigned int v, n = 0;
                asm volatile("atom.release.gpu.global.add.u32 %0, [%1], 1;" : "=r"(v) : "l"(g_s.cnt + prob * 32) : "memory");
                const unsigned int target = (v & ~63u) + 64u;
                do {
                    __nanosleep(n ? 1000 : 3000);
                    asm volatile("ld.relaxed.gpu.global.u32 %0, [%1];" : "=r"(v) : "l"(g_s.cnt + prob * 32) : "memory");
                    if (++n > SPIN_LIMIT) __trap();
                } while ((int)(v - target) < 0);
                asm volatile("ld.acquire.gpu.global.u32 %0, [%1];" : "=r"(v) : "l"(g_s.cnt + prob * 32) : "memory");
                mbar_arrive(bar_ready);
            }
            __syncwarp();
            mbar_wait(bar_go, 0);
            float e[4];
            {
                uint4 sa = zero4, sb2 = zero4, sc = zero4, sd = zero4;
                const float4* ssrc = g_s.stat + ((prob * 2 + ((c >> 3) & 1)) * 16 + 4 * m4 + (m4 < 3 ? 3 - (c >> 4) : (c >> 4))) * 32 + l8;
                poll128(sc, ssrc + 16 * (1 - hf), true);
                poll128(sd, ssrc + 16 * (1 - hf) + 8, true);
                poll2(sa, ssrc + 16 * hf, sb2, ssrc + 16 * hf + 8, 300);
                poll2(sc, ssrc + 16 * (1 - hf), sd, ssrc + 16 * (1 - hf) + 8, 300);
                if (hf == 0 && lane < 8) stg128(g_s.q + bid * 8 + lane, zero4);
                float M = fmaxf(fmaxf(fmaxf(__uint_as_float(sa.x), __uint_as_float(sa.z)), fmaxf(__uint_as_float(sb2.x), __uint_as_float(sb2.z))),
                                fmaxf(fmaxf(__uint_as_float(sc.x), __uint_as_float(sc.z)), fmaxf(__uint_as_float(sd.x), __uint_as_float(sd.z))));
#pragma unroll
                for (int o = 4; o > 0; o >>= 1) M = fmaxf(M, __shfl_xor_sync(0xffffffffu, M, o));
                e[0] = ex2(__uint_as_float(sa.x) - M); e[1] = ex2(__uint_as_float(sa.z) - M);
                e[2] = ex2(__uint_as_float(sb2.x) - M); e[3] = ex2(__uint_as_float(sb2.z) - M);
                const float La = (e[0] * __uint_as_float(sa.y) + e[1] * __uint_as_float(sa.w)) + (e[2] * __uint_as_float(sb2.y) + e[3] * __uint_as_float(sb2.w));
                const float Lb = (ex2(__uint_as_float(sc.x) - M) * __uint_as_float(sc.y) + ex2(__uint_as_float(sc.z) - M) * __uint_as_float(sc.w)) +
                                 (ex2(__uint_as_float(sd.x) - M) * __uint_as_float(sd.y) + ex2(__uint_as_float(sd.z) - M) * __uint_as_float(sd.w));
                float L = La + Lb;
#pragma unroll
                for (int o = 4; o > 0; o >>= 1) L += __shfl_xor_sync(0xffffffffu, L, o);
                const float inv = 1.0f / L;
#pragma unroll
                for (int i = 0; i < 4; i++) e[i] *= inv;
            }
            const bool up = lane >= 16;
            const int pr = 2 * j4 + (up ? 1 : 0);
            const uint32_t of_addr = sb + SM_OF + hf * 128 + ((pr & 3) * 8 + (pr >> 2)) * 4;
#pragma unroll 1
            for (int t = 0; t < 4; t++) {
                float wg[4];
#pragma unroll
                for (int i = 0; i < 4; i++) {
                    const float u0 = __shfl_sync(0xffffffffu, e[i & 2], 8 * t + 4 * (i & 1) + (g8 >> 1));
                    const float u1 = __shfl_sync(0xffffffffu, e[(i & 2) + 1], 8 * t + 4 * (i & 1) + (g8 >> 1));
                    wg[i] = (g8 & 1) ? u1 : u0;
                }
                mbar_wait(bar_go + 8 * t, 0);
                uint4 pv[4] = {zero4, zero4, zero4, zero4};
                {
                    uint32_t n = 0;
                    while (true) {
                        bool m[4], miss = false;
#pragma unroll
                        for (int i = 0; i < 4; i++) { m[i] = !all_set(pv[i]); miss |= m[i]; }
                        if (!__any_sync(0xffffffffu, miss)) break;
                        if (t < 3 && n) __nanosleep(300);
#pragma unroll
                        for (int i = 0; i < 4; i++) poll128(pv[i], psrc + 256 * t + 32 * i, m[i]);
                        if (++n > SPIN_LIMIT) __trap();
                    }
                }
                const float x = (wg[0] * __uint_as_float(pv[0].x) + wg[1] * __uint_as_float(pv[1].x)) + (wg[2] * __uint_as_float(pv[2].x) + wg[3] * __uint_as_float(pv[3].x));
                const float y = (wg[0] * __uint_as_float(pv[0].y) + wg[1] * __uint_as_float(pv[1].y)) + (wg[2] * __uint_as_float(pv[2].y) + wg[3] * __uint_as_float(pv[3].y));
                const float z = (wg[0] * __uint_as_float(pv[0].z) + wg[1] * __uint_as_float(pv[1].z)) + (wg[2] * __uint_as_float(pv[2].z) + wg[3] * __uint_as_float(pv[3].z));
                const float w = (wg[0] * __uint_as_float(pv[0].w) + wg[1] * __uint_as_float(pv[1].w)) + (wg[2] * __uint_as_float(pv[2].w) + wg[3] * __uint_as_float(pv[3].w));
                float k0 = (up ? z : x) + __shfl_xor_sync(0xffffffffu, up ? x : z, 16);
                float k1 = (up ? w : y) + __shfl_xor_sync(0xffffffffu, up ? y : w, 16);
#pragma unroll
                for (int o = 8; o > 2; o >>= 1) {
                    k0 += __shfl_xor_sync(0xffffffffu, k0, o);
                    k1 += __shfl_xor_sync(0xffffffffu, k1, o);
                }
                if ((lane & 12) == 0) sts32(of_addr + 8 * t, pack_bf16(k0, k1));
                __syncwarp();
                if (lane == 0) mbar_arrive(t < 3 ? bar_ofa : bar_of);
            }
        } else {
            if (lane < 4) mbar_expect(bar_wo + 8 * lane, 18432);
            if (lane == 0) {
                uint32_t rep = 0, n = 0;
                while (rep < 64u) {
                    const uint32_t cur = lds32v(sb + SM_PROG + 4);
                    if (cur == rep) { __nanosleep(40); if (++n > (SPIN_LIMIT << 2)) __trap(); continue; }
                    uint32_t v;
                    asm volatile("atom.relaxed.gpu.global.add.u32 %0, [%1], %2;" : "=r"(v) : "l"(g_s.cnt + 64), "r"(cur - rep) : "memory");
                    sts32(sb + SM_PROG, v);
                    if (v + (cur - rep) == 128u * 64u) stg32(g_s.cnt + 64, 0u);
                    rep = cur;
                }
            }
        }
        return;
    } else if (wu < 8) {
        {
            uint32_t xb[3][12];
            mbar_wait(bar_x, 0);
#pragma unroll
            for (int b = 0; b < 3; b++)
#pragma unroll
                for (int t = 0; t < 12; t++) xb[b][t] = lds32v(sb + SM_X + ((warp >> 2) * 48 + j4 + b * 96 + 4 * t) * 4);
            float c0[4] = {0.f, 0.f, 0.f, 0.f}, c1[4] = {0.f, 0.f, 0.f, 0.f};
            const uint32_t base = sb + SM_RING + ((warp >> 2) * 96 + (m4 >> 1) * 8 + l8) * 128 + (((2 * (warp & 3) + (m4 & 1)) ^ l8) << 4);
#pragma unroll
            for (int b = 0; b < 3; b++) {
                mbar_wait(bar_full + 16 * b + 8 * (warp >> 2), 0);
#pragma unroll
                for (int t = 0; t < 3; t++) {
                    uint32_t a0[4], a1[4];
                    ldsm4t(a0, base + b * TILE + (2 * t) * 2048);
                    ldsm4t(a1, base + b * TILE + (2 * t + 1) * 2048);
                    mma16816(c0, a0, xb[b][4 * t], xb[b][4 * t + 1]);
                    mma16816(c1, a1, xb[b][4 * t + 2], xb[b][4 * t + 3]);
                }
                __syncwarp();
                if (lane == 0) mbar_arrive(bar_empty + 8 * b);
            }
            if (j4 < 2) sts32(sb + SM_RED + (warp * 16 + g8 + 8 * j4) * 4, __float_as_uint(j4 ? c0[2] + c1[2] : c0[0] + c1[0]));
        }
        bar_consumers();
        if (warp == 0) {
            const float2 va = lds64f(sb + SM_RED + lane * 8), vb = lds64f(sb + SM_RED + 256 + lane * 8);
            uint32_t u = pack_bf16(va.x + vb.x, va.y + vb.y);
            if (u == 0u) u = 0x8000u;
            const int d = 64 * (c & 1) + 2 * lane;
            const int w16 = 2 * (d >> 4) + ((d >> 3) & 1);
            stg32(reinterpret_cast<uint32_t*>(g_s.q) + (bid >> 2) * 128 + (w16 >> 2) * 32 + ((c >> 1) & 1) * 16 + ((d & 7) >> 1) * 4 + (w16 & 3), u);
        }
        {
            uint4 v = zero4, v2 = zero4;
            mbar_wait(bar_full + 8 * 9, 0);
            poll2(v, g_s.q + prob * 512 + tid, v2, g_s.q + prob * 512 + 256 + tid, 300);
            sts128(sb + SM_Q + tid * 16, v);
            sts128(sb + SM_Q + 4096 + tid * 16, v2);
        }
        bar_consumers();
        const uint32_t frag_off = (g8 & 1) * 64 + j4 * 16;
        int s = 3, ph = 0;

        {
            const uint32_t kbase = sb + SM_RING + (2 * warp + (m4 & 1)) * 2048 + l8 * 128 + (((m4 >> 1) ^ l8) << 4);
            const uint32_t sc_addr = sb + SM_SC + (warp * 32 + (j4 & 1) * 16 + (g8 >> 1) * 4 + (g8 & 1) + (j4 >> 1) * 2) * 4;
#pragma unroll 1
            for (int i = 0; i < 16; i++) {
                uint4 qb[4];
#pragma unroll
                for (int q = 0; q < 4; q++) qb[q] = lds128(sb + SM_Q + i * 512 + q * 128 + frag_off);
                mbar_wait(bar_full + 16 * s + 8 * (warp >> 2), ph);
                float c0[4] = {0.f, 0.f, 0.f, 0.f}, c1[4] = {0.f, 0.f, 0.f, 0.f};
                const uint32_t kb = kbase + s * TILE;
#pragma unroll
                for (int q = 0; q < 4; q++) {
                    uint32_t a0[4], a1[4];
                    ldsm4(a0, (kb ^ (((2 * q) & 3) << 5)) + (q >> 1) * 1024);
                    ldsm4(a1, (kb ^ (((2 * q + 1) & 3) << 5)) + (q >> 1) * 1024);
                    mma16816(c0, a0, qb[q].x, qb[q].y);
                    mma16816(c1, a1, qb[q].z, qb[q].w);
                }
                __syncwarp();
                if (lane == 0) mbar_arrive(bar_empty + 8 * s);
                sts32(sc_addr + i * 1024, __float_as_uint(sel4(c0, j4) + sel4(c1, j4)));
                if (++s == NST) { s = 0; ph ^= 1; }
            }
        }
        mbar_wait(bar_ready, 0);
        bar_consumers();

        {
            constexpr float SCALE = 0.08838834764831845f * 1.4426950408889634f;
            const int hd = warp & 1, st = warp >> 1;
            float4 sv[4];
            float ms[4], sum[4];
#pragma unroll
            for (int t = 0; t < 4; t++) {
                sv[t] = lds128f(sb + SM_SC + ((4 * st + t) * 256 + g8 * 32 + hd * 16 + j4 * 4) * 4);
                ms[t] = fmaxf(fmaxf(sv[t].x, sv[t].y), fmaxf(sv[t].z, sv[t].w));
            }
#pragma unroll
            for (int o = 16; o > 0; o >>= 1)
#pragma unroll
                for (int t = 0; t < 4; t++) ms[t] = fmaxf(ms[t], __shfl_xor_sync(0xffffffffu, ms[t], o));
#pragma unroll
            for (int t = 0; t < 4; t++) {
                ms[t] *= SCALE;
                const float m = ms[t];
                const float p0 = ex2(fmaf(sv[t].x, SCALE, -m)), p1 = ex2(fmaf(sv[t].y, SCALE, -m));
                const float p2 = ex2(fmaf(sv[t].z, SCALE, -m)), p3 = ex2(fmaf(sv[t].w, SCALE, -m));
                sum[t] = (p0 + p1) + (p2 + p3);
                sts64(sb + SM_P + (4 * st + t) * 512 + (g8 >> 1) * 128 + hd * 64 + j4 * 16 + (g8 & 1) * 8, pack_bf16(p0, p1), pack_bf16(p2, p3));
            }
            bar_consumers();
#pragma unroll
            for (int o = 16; o > 0; o >>= 1)
#pragma unroll
                for (int t = 0; t < 4; t++) sum[t] += __shfl_xor_sync(0xffffffffu, sum[t], o);
            if (lane < 4)
                stg64(reinterpret_cast<float2*>(g_s.stat) + ((prob * 2 + hd) * 16 + 4 * st + lane) * 64 + c, nz(sel4(ms, lane)), nz(sel4(sum, lane)));
        }

        {
            const uint32_t vbase = sb + SM_RING + (m4 >> 1) * 2048 + (warp >> 2) * 1024 + l8 * 128 + (((2 * (warp & 3) + (m4 & 1)) ^ l8) << 4);
            float* const dst = reinterpret_cast<float*>(g_s.part) + (prob * 64 + 8 * (j4 & 1) + warp) * 4096 + c * 16 + g8 + 8 * (j4 >> 1);
            const int go_off = 6 - (c >> 4);
#pragma unroll 1
            for (int i = 0; i < 16; i++) {
                float c0[4] = {0.f, 0.f, 0.f, 0.f}, c1[4] = {0.f, 0.f, 0.f, 0.f};
                uint4 pb[4];
#pragma unroll
                for (int q = 0; q < 4; q++) pb[q] = lds128(sb + SM_P + i * 512 + q * 128 + frag_off);
                const uint32_t vb = vbase + s * TILE;
#pragma unroll
                for (int q = 0; q < 4; q++) {
                    uint32_t a0[4], a1[4];
                    if ((q & 1) == 0) mbar_wait(bar_full + 16 * s + 4 * q, ph);
                    ldsm4t(a0, vb + (2 * q) * 4096);
                    ldsm4t(a1, vb + (2 * q + 1) * 4096);
                    mma16816(c0, a0, pb[q].x, pb[q].y);
                    mma16816(c1, a1, pb[q].z, pb[q].w);
                }
                __syncwarp();
                if (lane == 0) mbar_arrive(bar_empty + 8 * s);
                stg32(dst + (i < 12 ? 3 - (i & 3) : (i & 3)) * (16 * 4096) + (i >> 2) * 1024, nz(sel4(c0, j4) + sel4(c1, j4)));
                if (tid == 0 && (i == 15 || (i >= go_off && ((i - go_off) & 3) == 0)))
                    mbar_arrive(bar_go + (i == 15 ? 24 : 2 * (i - go_off)));
                if (++s == NST) { s = 0; ph ^= 1; }
            }
        }
    }

    {
        float acc[2][4][4];
#pragma unroll
        for (int e = 0; e < 32; e++) (&acc[0][0][0])[e] = 0.f;
        const int rho = 9 * ((m4 >> 1) * 8 + l8) + warp;
        uint32_t base[4];
#pragma unroll
        for (int mt = 0; mt < 4; mt++) base[mt] = (sb + SM_RING + rho * 128 + (((m4 & 1) ^ (rho & 7)) << 4)) ^ (mt << 5);
        float4* dst = g_s.acc + (prob * 40 + (tid >> 3)) * 72 + (tid & 7);
        __nv_bfloat16* optr = prm.out + prob * 576 + warp * 64 + 16 * j4 + g8;
        uint32_t js = j4, of_addr = sb + SM_OF + (g8 & 1) * 128 + j4 * 32;
        asm volatile("" : "+r"(base[0]), "+r"(base[1]), "+r"(base[2]), "+r"(base[3]), "+l"(dst), "+l"(optr), "+r"(js), "+r"(of_addr));
        uint32_t wa[2][4][4];
#define LOAD_W(t) _Pragma("unroll") for (int mt = 0; mt < 4; mt++) ldsm4t(wa[(t) & 1][mt], base[mt] + ((t) ? ((t) - 1) * 18432 : 5 * TILE))
#define MMA_W(t, b0, b1) _Pragma("unroll") for (int mt = 0; mt < 4; mt++) mma16816(acc[(t) & 1][mt], wa[(t) & 1][mt], b0, b1)
        auto pick = [&](int a, int e) {
            float r;
            asm("{\n .reg .pred p, q;\n .reg .f32 u, v;\n .reg .b32 t;\n and.b32 t, %5, 1;\n setp.ne.u32 p, t, 0;\n setp.gt.u32 q, %5, 1;\n"
                " selp.f32 u, %2, %1, p;\n selp.f32 v, %4, %3, p;\n selp.f32 %0, v, u, q;\n}"
                : "=f"(r) : "f"(acc[a][0][e]), "f"(acc[a][1][e]), "f"(acc[a][2][e]), "f"(acc[a][3][e]), "r"(js));
            return r;
        };
        mbar_wait(bar_ofa, 0);
        const uint4 o0 = lds128(of_addr);
        const float2 o1 = lds64f(of_addr + 16);
        mbar_wait(bar_wo, 0);
        LOAD_W(0);
        MMA_W(0, o0.x, o0.y);
        mbar_wait(bar_wo + 8, 0);
        LOAD_W(1);
        MMA_W(1, o0.z, o0.w);
        mbar_wait(bar_wo + 16, 0);
        LOAD_W(2);
        const bool have_w = mbar_test(bar_wo + 24, 0);
        if (have_w) { LOAD_W(3); }
        MMA_W(2, __float_as_uint(o1.x), __float_as_uint(o1.y));
        float2 o2;
        bool have_o = false;
        if (!have_w) {
            uint32_t n = 0;
            while (!mbar_test(bar_wo + 24, 0)) {
                if (mbar_test(bar_of, 0)) {
                    o2 = lds64f(of_addr + 24);
                    have_o = true;
                    mbar_wait(bar_wo + 24, 0);
                    break;
                }
                if (++n > (SPIN_LIMIT << 4)) __trap();
            }
            LOAD_W(3);
        }
        if (!have_o) { mbar_wait(bar_of, 0); o2 = lds64f(of_addr + 24); }
        MMA_W(3, __float_as_uint(o2.x), __float_as_uint(o2.y));
        const float v0 = (pick(0, 0) + pick(0, 1)) + (pick(1, 0) + pick(1, 1)), v1 = (pick(0, 2) + pick(0, 3)) + (pick(1, 2) + pick(1, 3));
        float r0, r1, r2;
        asm volatile("{\n .reg .f32 t;\n atom.relaxed.gpu.global.add.v4.f32 {%0,%1,%2,t}, [%3], {%4,%5,%6,%7};\n}"
                     : "=f"(r0), "=f"(r1), "=f"(r2) : "l"(dst), "f"(v0), "f"(v1), "f"(1.0f), "f"(0.0f) : "memory");
        if (r2 == 63.0f) { optr[0] = __float2bfloat16(r0 + v0); optr[8] = __float2bfloat16(r1 + v1); }
#undef LOAD_W
#undef MMA_W
    }
}

typedef CUresult (*EncodeFn)(CUtensorMap*, CUtensorMapDataType, cuuint32_t, void*, const cuuint64_t*, const cuuint64_t*,
                             const cuuint32_t*, const cuuint32_t*, CUtensorMapInterleave, CUtensorMapSwizzle,
                             CUtensorMapL2promotion, CUtensorMapFloatOOBfill);

}

extern "C" void kernel_launch(void* const* d_in, const int* in_sizes, int n_in, void* d_out, int out_size) {
    (void)in_sizes; (void)n_in; (void)out_size;
    static EncodeFn enc = nullptr;
    if (!enc) {
        cudaDriverEntryPointQueryResult qr;
        void* fn = nullptr;
        cudaGetDriverEntryPoint("cuTensorMapEncodeTiled", &fn, cudaEnableDefault, &qr);
        enc = (EncodeFn)fn;
        cudaFuncSetAttribute(gqa2_decode_kernel, cudaFuncAttributeMaxDynamicSharedMemorySize, SM_TOTAL);
    }
    Params prm;
    const cuuint32_t es[4] = {1, 1, 1, 1};
    for (int p = 0; p < 2; p++) {
        prm.x[p] = (const __nv_bfloat16*)d_in[5 * p + 0];
        void* ptr[4] = {d_in[5 * p + 3], d_in[5 * p + 1], d_in[5 * p + 2], d_in[5 * p + 4]};
        const cuuint64_t gd[4][4] = {{4096, 576, 1, 1}, {64, 8, 2, 16 * 8192 / 8}, {64, 8, 2, 16 * 8192 / 8}, {64, 4096 * 9, 1, 1}};
        const cuuint64_t gs[4][3] = {{8192, 8192 * 576, 8192 * 576}, {256, 128, 2048}, {256, 128, 2048}, {128, 128 * 4096 * 9, 128 * 4096 * 9}};
        const cuuint32_t bd[4][4] = {{64, 96, 1, 1}, {64, 8, 2, 8}, {64, 8, 2, 8}, {64, 144, 1, 1}};
        for (int i = 0; i < 4; i++)
            enc(&prm.tm[p][i], CU_TENSOR_MAP_DATA_TYPE_BFLOAT16, 4, ptr[i], gd[i], gs[i], bd[i], es,
                CU_TENSOR_MAP_INTERLEAVE_NONE, CU_TENSOR_MAP_SWIZZLE_128B, CU_TENSOR_MAP_L2_PROMOTION_L2_128B,
                CU_TENSOR_MAP_FLOAT_OOB_FILL_NONE);
    }
    prm.out = (__nv_bfloat16*)d_out;
    gqa2_decode_kernel<<<128, NTHREADS, SM_TOTAL>>>(prm);
}
```

```cpp
#include <cuda_runtime.h>
#include <cuda_bf16.h>
#include <cuda.h>
#include <stdint.h>

namespace {

constexpr int TILE = 32768;
constexpr int NST  = 6;
constexpr int DEPTH = 4;
constexpr int NTHREADS = 384;

constexpr int SM_RING = 0;
constexpr int SM_SC   = NST * TILE;
constexpr int SM_P    = SM_SC + 16384;
constexpr int SM_Q    = SM_P;
constexpr int SM_X    = SM_P + 8192;
constexpr int SM_RED  = SM_X + 1152;
constexpr int SM_OF   = SM_RED + 512;
constexpr int SM_PROG = SM_OF + 256;
constexpr int SM_BAR  = SM_PROG + 16;
constexpr int SM_TOTAL = SM_BAR + 256;

struct alignas(64) Params {
    CUtensorMap tm[2][4];
    const __nv_bfloat16* x[2];
    __nv_bfloat16* out;
};

struct alignas(4096) Scratch {
    float4 acc[4 * 40 * 72];
    float4 part[128 * 1024];
    uint4  q[128 * 8];
    float4 stat[128 * 16];
    unsigned int cnt[3 * 32];
};
__device__ Scratch g_s;

constexpr uint32_t SPIN_LIMIT = 1u << 22;

__device__ __forceinline__ void mbar_init(uint32_t a, uint32_t c) {
    asm volatile("mbarrier.init.shared::cta.b64 [%0], %1;" ::"r"(a), "r"(c) : "memory");
}
__device__ __forceinline__ void mbar_expect(uint32_t a, uint32_t b) {
    asm volatile("mbarrier.arrive.expect_tx.shared::cta.b64 _, [%0], %1;" ::"r"(a), "r"(b) : "memory");
}
__device__ __forceinline__ void mbar_arrive(uint32_t a) {
    asm volatile("mbarrier.arrive.shared::cta.b64 _, [%0];" ::"r"(a) : "memory");
}
__device__ __forceinline__ void mbar_wait(uint32_t a, uint32_t ph) {
    uint32_t ok, n = 0;
    do {
        asm volatile("{\n .reg .pred p;\n mbarrier.try_wait.parity.shared::cta.b64 p, [%1], %2;\n selp.u32 %0, 1, 0, p;\n}"
                     : "=r"(ok) : "r"(a), "r"(ph) : "memory");
        if (++n > SPIN_LIMIT) __trap();
    } while (!ok);
}
__device__ __forceinline__ bool mbar_test(uint32_t a, uint32_t ph) {
    uint32_t ok;
    asm volatile("{\n .reg .pred p;\n mbarrier.test_wait.parity.shared::cta.b64 p, [%1], %2;\n selp.u32 %0, 1, 0, p;\n}"
                 : "=r"(ok) : "r"(a), "r"(ph) : "memory");
    return __all_sync(0xffffffffu, ok != 0);
}
__device__ __forceinline__ void tma4d(uint32_t dst, const CUtensorMap* tm, int c0, int c1, int c3, uint32_t mbar, uint64_t pol) {
    asm volatile("cp.async.bulk.tensor.4d.shared::cluster.global.mbarrier::complete_tx::bytes.L2::cache_hint"
                 " [%0], [%1, {%3, %4, %5, %6}], [%2], %7;"
                 ::"r"(dst), "l"(tm), "r"(mbar), "r"(c0), "r"(c1), "r"(0), "r"(c3), "l"(pol) : "memory");
}
__device__ __forceinline__ void ldsm4(uint32_t (&r)[4], uint32_t a) {
    asm volatile("ldmatrix.sync.aligned.m8n8.x4.shared.b16 {%0,%1,%2,%3}, [%4];"
                 : "=r"(r[0]), "=r"(r[1]), "=r"(r[2]), "=r"(r[3]) : "r"(a) : "memory");
}
__device__ __forceinline__ void ldsm4t(uint32_t (&r)[4], uint32_t a) {
    asm volatile("ldmatrix.sync.aligned.m8n8.x4.trans.shared.b16 {%0,%1,%2,%3}, [%4];"
                 : "=r"(r[0]), "=r"(r[1]), "=r"(r[2]), "=r"(r[3]) : "r"(a) : "memory");
}
__device__ __forceinline__ void mma16816(float (&c)[4], const uint32_t (&a)[4], uint32_t b0, uint32_t b1) {
    asm volatile("mma.sync.aligned.m16n8k16.row.col.f32.bf16.bf16.f32 {%0,%1,%2,%3}, {%4,%5,%6,%7}, {%8,%9}, {%0,%1,%2,%3};"
                 : "+f"(c[0]), "+f"(c[1]), "+f"(c[2]), "+f"(c[3])
                 : "r"(a[0]), "r"(a[1]), "r"(a[2]), "r"(a[3]), "r"(b0), "r"(b1));
}
__device__ __forceinline__ uint4 lds128(uint32_t a) {
    uint4 v;
    asm volatile("ld.shared.v4.u32 {%0,%1,%2,%3}, [%4];" : "=r"(v.x), "=r"(v.y), "=r"(v.z), "=r"(v.w) : "r"(a) : "memory");
    return v;
}
__device__ __forceinline__ float4 lds128f(uint32_t a) {
    float4 v;
    asm volatile("ld.shared.v4.f32 {%0,%1,%2,%3}, [%4];" : "=f"(v.x), "=f"(v.y), "=f"(v.z), "=f"(v.w) : "r"(a) : "memory");
    return v;
}
__device__ __forceinline__ float2 lds64f(uint32_t a) {
    float2 v;
    asm volatile("ld.shared.v2.f32 {%0,%1}, [%2];" : "=f"(v.x), "=f"(v.y) : "r"(a) : "memory");
    return v;
}
__device__ __forceinline__ uint32_t lds32v(uint32_t a) {
    uint32_t v;
    asm volatile("ld.volatile.shared.u32 %0, [%1];" : "=r"(v) : "r"(a) : "memory");
    return v;
}
__device__ __forceinline__ void sts128(uint32_t a, uint4 v) {
    asm volatile("st.shared.v4.u32 [%0], {%1,%2,%3,%4};" ::"r"(a), "r"(v.x), "r"(v.y), "r"(v.z), "r"(v.w) : "memory");
}
__device__ __forceinline__ void sts64(uint32_t a, uint32_t x, uint32_t y) {
    asm volatile("st.shared.v2.u32 [%0], {%1,%2};" ::"r"(a), "r"(x), "r"(y) : "memory");
}
__device__ __forceinline__ void sts32(uint32_t a, uint32_t x) {
    asm volatile("st.volatile.shared.u32 [%0], %1;" ::"r"(a), "r"(x) : "memory");
}
__device__ __forceinline__ void poll128(uint4& v, const void* p, bool pred) {
    asm volatile("{\n .reg .pred p;\n setp.ne.u32 p, %5, 0;\n @p ld.relaxed.gpu.global.v4.u32 {%0,%1,%2,%3}, [%4];\n}"
                 : "+r"(v.x), "+r"(v.y), "+r"(v.z), "+r"(v.w) : "l"(p), "r"((uint32_t)pred) : "memory");
}
__device__ __forceinline__ void stg128(void* p, uint4 v) {
    asm volatile("st.relaxed.gpu.global.v4.u32 [%0], {%1,%2,%3,%4};" ::"l"(p), "r"(v.x), "r"(v.y), "r"(v.z), "r"(v.w) : "memory");
}
__device__ __forceinline__ void stg64(void* p, uint32_t x, uint32_t y) {
    asm volatile("st.relaxed.gpu.global.v2.u32 [%0], {%1,%2};" ::"l"(p), "r"(x), "r"(y) : "memory");
}
__device__ __forceinline__ void stg32(void* p, uint32_t x) {
    asm volatile("st.relaxed.gpu.global.u32 [%0], %1;" ::"l"(p), "r"(x) : "memory");
}
__device__ __forceinline__ uint32_t nz(float f) {
    uint32_t u = __float_as_uint(f);
    return u == 0u ? 0x80000000u : u;
}
__device__ __forceinline__ bool all_set(const uint4& v) { return v.x != 0u && v.y != 0u && v.z != 0u && v.w != 0u; }
__device__ __forceinline__ void poll2(uint4& a, const void* pa, uint4& b, const void* pb, int sleep_ns) {
    uint32_t n = 0;
    while (true) {
        const bool ma = !all_set(a), mb = !all_set(b);
        if (!__any_sync(0xffffffffu, ma || mb)) break;
        if (sleep_ns && n) __nanosleep(sleep_ns);
        poll128(a, pa, ma);
        poll128(b, pb, mb);
        if (++n > SPIN_LIMIT) __trap();
    }
}
__device__ __forceinline__ uint32_t pack_bf16(float lo, float hi) {
    uint32_t r;
    asm("cvt.rn.bf16x2.f32 %0, %1, %2;" : "=r"(r) : "f"(hi), "f"(lo));
    return r;
}
__device__ __forceinline__ float ex2(float x) {
    float r;
    asm("ex2.approx.ftz.f32 %0, %1;" : "=f"(r) : "f"(x));
    return r;
}
__device__ __forceinline__ float sel4(const float (&c)[4], int j) {
    float a = (j & 1) ? c[1] : c[0];
    float b = (j & 1) ? c[3] : c[2];
    return (j & 2) ? b : a;
}
__device__ __forceinline__ bool elect_one() {
    uint32_t p;
    asm volatile("{\n .reg .pred p;\n elect.sync _|p, 0xffffffff;\n selp.u32 %0, 1, 0, p;\n}" : "=r"(p));
    return p != 0;
}
__device__ __forceinline__ void bar_consumers() { asm volatile("bar.sync 1, 256;" ::: "memory"); }

__global__ void __launch_bounds__(NTHREADS, 1)
gqa2_decode_kernel(const __grid_constant__ Params prm) {
    extern __shared__ __align__(1024) unsigned char smem_raw[];
    constexpr uint32_t sb = 1024;
    const int tid = threadIdx.x, warp = tid >> 5, lane = tid & 31;
    const int bid = blockIdx.x, prob = bid >> 6, c = bid & 63;
    const uint32_t bar_full = sb + SM_BAR, bar_empty = bar_full + 16 * NST;
    const uint32_t bar_ready = bar_empty + 8 * NST, bar_x = bar_ready + 8, bar_of = bar_ready + 16,
                   bar_go = bar_ready + 24, bar_ofa = bar_ready + 56;

    int wu = __shfl_sync(0xffffffffu, warp, 0);
    if (wu == 8) {
        uint64_t pol;
        asm volatile("createpolicy.fractional.L2::evict_first.b64 %0, 1.0;" : "=l"(pol));
        if (elect_one()) {
            mbar_init(bar_full, 1);
            asm volatile("fence.mbarrier_init.release.cluster;" ::: "memory");
            mbar_expect(bar_full, 12288);
            tma4d(sb + SM_RING, &prm.tm[prob][0], c * 64, 0, 0, bar_full, pol);
        }
        __syncwarp();
        if (elect_one()) {
#pragma unroll
            for (int s = 1; s < DEPTH; s++) mbar_init(bar_full + 8 * s, 1);
            asm volatile("fence.mbarrier_init.release.cluster;" ::: "memory");
#pragma unroll
            for (int n = 1; n < DEPTH; n++) {
                mbar_expect(bar_full + 8 * n, 12288);
                tma4d(sb + SM_RING + (n >> 1) * TILE + (n & 1) * 12288, &prm.tm[prob][0], c * 64, n * 96, 0, bar_full + 8 * n, pol);
            }
        }
        __syncwarp();
        if (elect_one()) {
            if ((uint32_t)__cvta_generic_to_shared(smem_raw) != sb) __trap();
#pragma unroll
            for (int s = DEPTH; s < 2 * NST; s++) mbar_init(bar_full + 8 * s, 1);
#pragma unroll
            for (int s = 0; s < NST; s++) mbar_init(bar_empty + 8 * s, 8);
#pragma unroll
            for (int s = 0; s < 7; s++) mbar_init(bar_ready + 8 * s, s == 2 ? 2 : 1);
            mbar_init(bar_ofa, 6);
            asm volatile("fence.mbarrier_init.release.cluster;" ::: "memory");
            mbar_expect(bar_x, 1152);
            asm volatile("cp.async.bulk.shared::cluster.global.mbarrier::complete_tx::bytes [%0], [%1], 1152, [%2];"
                         ::"r"(sb + SM_X), "l"(prm.x[prob]), "r"(bar_x) : "memory");
            sts64(sb + SM_PROG, 0u, 0u);
#pragma unroll
            for (int k = 1; k < 4; k++) asm volatile("prefetch.tensormap [%0];" ::"l"(&prm.tm[prob][k]) : "memory");
        }
        __syncwarp();
        asm volatile("bar.arrive 3, %0;" ::"n"(NTHREADS) : "memory");
        int ib = DEPTH, iph = 0;
        int nw = 0, wb = 0, wph = 0;
#pragma unroll 1
        for (int n = DEPTH; n < 74; n++) {
            const bool wq = n < 6, wo = n >= 70;
            const int bytes = wq ? 12288 : (wo ? 18432 : TILE / 2);
            const uint32_t dst = sb + SM_RING + (ib >> 1) * TILE + (ib & 1) * bytes, bar = bar_full + 8 * ib;
            const CUtensorMap* tm = &prm.tm[prob][(n >= 6) + (n >= 38) + (n >= 70)];
            const int c0 = wq ? c * 64 : 0;
            const int c1 = wq ? n * 96 : (wo ? ((n - 70) * 1024 + (n < 73 ? (c ^ 48) : c) * 16) * 9 : 0);
            const int c3 = wq || wo ? 0 : ((n - 6) & 31) * 512 + c * 8;
            if (n >= 2 * NST && (ib & 1) == 0) mbar_wait(bar_empty + 4 * ib, iph ^ 1);
            if (elect_one()) mbar_expect(bar, bytes);
            while (true) {
                int win = DEPTH;
                if (n >= 14) {
                    const int lag = (int)lds32v(sb + SM_PROG) - ((n - 10) * 128 - 256);
                    win = min(max(DEPTH + (lag >> 7), 2), wo ? 6 : 8);
                }
                if (n - nw < win) break;
                mbar_wait(bar_full + 8 * wb, wph);
                wb += nw >= 70 ? 2 : 1;
                nw++;
                if (wb >= 2 * NST) { wb = 0; wph ^= 1; }
            }
            if (elect_one()) {
                tma4d(dst, tm, c0, c1, c3, bar, pol);
                if (n >= 10) sts32(sb + SM_PROG + 4, n - 9);
            }
            ib += wo ? 2 : 1;
            if (ib >= 2 * NST) { ib = 0; iph ^= 1; }
        }
    } else {
        asm volatile("bar.sync 3, %0;" ::"n"(NTHREADS) : "memory");
    }
    asm volatile("" : "+r"(wu));
    const int g8 = lane >> 2, j4 = lane & 3, l8 = lane & 7, m4 = lane >> 3;
    const uint4 zero4 = make_uint4(0u, 0u, 0u, 0u);

    if (wu > 8) {
        if (wu < 11) {
            const int hf = wu - 9;
            float4* const psrc = g_s.part + bid * 1024 + hf * 128 + lane;
#pragma unroll
            for (int i = 0; i < 16; i++) { stg128(psrc + (i >> 2) * 256 + (i & 3) * 32, zero4); __nanosleep(300); }
            if (hf == 0) {
                const int e = c * 5 + lane;
                if (lane < 5) stg128(g_s.acc + (prob * 40 + (e >> 3)) * 72 + (e & 7), zero4);
            } else if (lane < 16) stg128(g_s.stat + bid * 16 + lane, zero4);
            asm volatile("bar.sync 2, 64;" ::: "memory");
            if (tid == 288) {
                unsigned int v, n = 0;
                asm volatile("atom.release.gpu.global.add.u32 %0, [%1], 1;" : "=r"(v) : "l"(g_s.cnt + prob * 32) : "memory");
                const unsigned int target = (v & ~63u) + 64u;
                do {
                    __nanosleep(n ? 1000 : 3000);
                    asm volatile("ld.relaxed.gpu.global.u32 %0, [%1];" : "=r"(v) : "l"(g_s.cnt + prob * 32) : "memory");
                    if (++n > SPIN_LIMIT) __trap();
                } while ((int)(v - target) < 0);
                asm volatile("ld.acquire.gpu.global.u32 %0, [%1];" : "=r"(v) : "l"(g_s.cnt + prob * 32) : "memory");
                mbar_arrive(bar_ready);
            }
            __syncwarp();
            mbar_wait(bar_go, 0);
            float e[4];
            {
                uint4 sa = zero4, sb2 = zero4, sc = zero4, sd = zero4;
                const float4* ssrc = g_s.stat + ((prob * 2 + ((c >> 3) & 1)) * 16 + 4 * m4 + (m4 < 3 ? 3 - (c >> 4) : (c >> 4))) * 32 + l8;
                poll128(sc, ssrc + 16 * (1 - hf), true);
                poll128(sd, ssrc + 16 * (1 - hf) + 8, true);
                poll2(sa, ssrc + 16 * hf, sb2, ssrc + 16 * hf + 8, 300);
                poll2(sc, ssrc + 16 * (1 - hf), sd, ssrc + 16 * (1 - hf) + 8, 300);
                if (hf == 0 && lane < 8) stg128(g_s.q + bid * 8 + lane, zero4);
                float M = fmaxf(fmaxf(fmaxf(__uint_as_float(sa.x), __uint_as_float(sa.z)), fmaxf(__uint_as_float(sb2.x), __uint_as_float(sb2.z))),
                                fmaxf(fmaxf(__uint_as_float(sc.x), __uint_as_float(sc.z)), fmaxf(__uint_as_float(sd.x), __uint_as_float(sd.z))));
#pragma unroll
                for (int o = 4; o > 0; o >>= 1) M = fmaxf(M, __shfl_xor_sync(0xffffffffu, M, o));
                e[0] = ex2(__uint_as_float(sa.x) - M); e[1] = ex2(__uint_as_float(sa.z) - M);
                e[2] = ex2(__uint_as_float(sb2.x) - M); e[3] = ex2(__uint_as_float(sb2.z) - M);
                const float La = (e[0] * __uint_as_float(sa.y) + e[1] * __uint_as_float(sa.w)) + (e[2] * __uint_as_float(sb2.y) + e[3] * __uint_as_float(sb2.w));
                const float Lb = (ex2(__uint_as_float(sc.x) - M) * __uint_as_float(sc.y) + ex2(__uint_as_float(sc.z) - M) * __uint_as_float(sc.w)) +
                                 (ex2(__uint_as_float(sd.x) - M) * __uint_as_float(sd.y) + ex2(__uint_as_float(sd.z) - M) * __uint_as_float(sd.w));
                float L = La + Lb;
#pragma unroll
                for (int o = 4; o > 0; o >>= 1) L += __shfl_xor_sync(0xffffffffu, L, o);
                const float inv = 1.0f / L;
#pragma unroll
                for (int i = 0; i < 4; i++) e[i] *= inv;
            }
            const bool up = lane >= 16;
            const int pr = 2 * j4 + (up ? 1 : 0);
            const uint32_t of_addr = sb + SM_OF + hf * 128 + ((pr & 3) * 8 + (pr >> 2)) * 4;
#pragma unroll 1
            for (int t = 0; t < 4; t++) {
                float wg[4];
#pragma unroll
                for (int i = 0; i < 4; i++) {
                    const float u0 = __shfl_sync(0xffffffffu, e[i & 2], 8 * t + 4 * (i & 1) + (g8 >> 1));
                    const float u1 = __shfl_sync(0xffffffffu, e[(i & 2) + 1], 8 * t + 4 * (i & 1) + (g8 >> 1));
                    wg[i] = (g8 & 1) ? u1 : u0;
                }
                mbar_wait(bar_go + 8 * t, 0);
                uint4 pv[4] = {zero4, zero4, zero4, zero4};
                {
                    uint32_t n = 0;
                    while (true) {
                        bool m[4], miss = false;
#pragma unroll
                        for (int i = 0; i < 4; i++) { m[i] = !all_set(pv[i]); miss |= m[i]; }
                        if (!__any_sync(0xffffffffu, miss)) break;
                        if (t < 3 && n) __nanosleep(300);
#pragma unroll
                        for (int i = 0; i < 4; i++) poll128(pv[i], psrc + 256 * t + 32 * i, m[i]);
                        if (++n > SPIN_LIMIT) __trap();
                    }
                }
                const float x = (wg[0] * __uint_as_float(pv[0].x) + wg[1] * __uint_as_float(pv[1].x)) + (wg[2] * __uint_as_float(pv[2].x) + wg[3] * __uint_as_float(pv[3].x));
                const float y = (wg[0] * __uint_as_float(pv[0].y) + wg[1] * __uint_as_float(pv[1].y)) + (wg[2] * __uint_as_float(pv[2].y) + wg[3] * __uint_as_float(pv[3].y));
                const float z = (wg[0] * __uint_as_float(pv[0].z) + wg[1] * __uint_as_float(pv[1].z)) + (wg[2] * __uint_as_float(pv[2].z) + wg[3] * __uint_as_float(pv[3].z));
                const float w = (wg[0] * __uint_as_float(pv[0].w) + wg[1] * __uint_as_float(pv[1].w)) + (wg[2] * __uint_as_float(pv[2].w) + wg[3] * __uint_as_float(pv[3].w));
                float k0 = (up ? z : x) + __shfl_xor_sync(0xffffffffu, up ? x : z, 16);
                float k1 = (up ? w : y) + __shfl_xor_sync(0xffffffffu, up ? y : w, 16);
#pragma unroll
                for (int o = 8; o > 2; o >>= 1) {
                    k0 += __shfl_xor_sync(0xffffffffu, k0, o);
                    k1 += __shfl_xor_sync(0xffffffffu, k1, o);
                }
                if ((lane & 12) == 0) sts32(of_addr + 8 * t, pack_bf16(k0, k1));
                __syncwarp();
                if (lane == 0) mbar_arrive(t < 3 ? bar_ofa : bar_of);
            }
        } else {
            if (lane == 0) {
                uint32_t rep = 0, n = 0;
                while (rep < 64u) {
                    const uint32_t cur = lds32v(sb + SM_PROG + 4);
                    if (cur == rep) { __nanosleep(40); if (++n > (SPIN_LIMIT << 2)) __trap(); continue; }
                    uint32_t v;
                    asm volatile("atom.relaxed.gpu.global.add.u32 %0, [%1], %2;" : "=r"(v) : "l"(g_s.cnt + 64), "r"(cur - rep) : "memory");
                    sts32(sb + SM_PROG, v);
                    if (v + (cur - rep) == 128u * 64u) stg32(g_s.cnt + 64, 0u);
                    rep = cur;
                }
            }
        }
        return;
    } else if (wu < 8) {
        {
            uint32_t xb[3][12];
            mbar_wait(bar_x, 0);
#pragma unroll
            for (int b = 0; b < 3; b++)
#pragma unroll
                for (int t = 0; t < 12; t++) xb[b][t] = lds32v(sb + SM_X + ((warp >> 2) * 48 + j4 + b * 96 + 4 * t) * 4);
            float c0[4] = {0.f, 0.f, 0.f, 0.f}, c1[4] = {0.f, 0.f, 0.f, 0.f};
            const uint32_t base = sb + SM_RING + ((warp >> 2) * 96 + (m4 >> 1) * 8 + l8) * 128 + (((2 * (warp & 3) + (m4 & 1)) ^ l8) << 4);
#pragma unroll
            for (int b = 0; b < 3; b++) {
                mbar_wait(bar_full + 16 * b + 8 * (warp >> 2), 0);
#pragma unroll
                for (int t = 0; t < 3; t++) {
                    uint32_t a0[4], a1[4];
                    ldsm4t(a0, base + b * TILE + (2 * t) * 2048);
                    ldsm4t(a1, base + b * TILE + (2 * t + 1) * 2048);
                    mma16816(c0, a0, xb[b][4 * t], xb[b][4 * t + 1]);
                    mma16816(c1, a1, xb[b][4 * t + 2], xb[b][4 * t + 3]);
                }
                __syncwarp();
                if (lane == 0) mbar_arrive(bar_empty + 8 * b);
            }
            if (j4 < 2) sts32(sb + SM_RED + (warp * 16 + g8 + 8 * j4) * 4, __float_as_uint(j4 ? c0[2] + c1[2] : c0[0] + c1[0]));
        }
        bar_consumers();
        if (warp == 0) {
            const float2 va = lds64f(sb + SM_RED + lane * 8), vb = lds64f(sb + SM_RED + 256 + lane * 8);
            uint32_t u = pack_bf16(va.x + vb.x, va.y + vb.y);
            if (u == 0u) u = 0x8000u;
            const int d = 64 * (c & 1) + 2 * lane;
            const int w16 = 2 * (d >> 4) + ((d >> 3) & 1);
            stg32(reinterpret_cast<uint32_t*>(g_s.q) + (bid >> 2) * 128 + (w16 >> 2) * 32 + ((c >> 1) & 1) * 16 + ((d & 7) >> 1) * 4 + (w16 & 3), u);
        }
        {
            uint4 v = zero4, v2 = zero4;
            mbar_wait(bar_full + 8 * 9, 0);
            poll2(v, g_s.q + prob * 512 + tid, v2, g_s.q + prob * 512 + 256 + tid, 300);
            sts128(sb + SM_Q + tid * 16, v);
            sts128(sb + SM_Q + 4096 + tid * 16, v2);
        }
        bar_consumers();
        const uint32_t frag_off = (g8 & 1) * 64 + j4 * 16;
        int s = 3, ph = 0;

        {
            const uint32_t kbase = sb + SM_RING + (2 * warp + (m4 & 1)) * 2048 + l8 * 128 + (((m4 >> 1) ^ l8) << 4);
            const uint32_t sc_addr = sb + SM_SC + (warp * 32 + (j4 & 1) * 16 + (g8 >> 1) * 4 + (g8 & 1) + (j4 >> 1) * 2) * 4;
#pragma unroll 1
            for (int i = 0; i < 16; i++) {
                uint4 qb[4];
#pragma unroll
                for (int q = 0; q < 4; q++) qb[q] = lds128(sb + SM_Q + i * 512 + q * 128 + frag_off);
                mbar_wait(bar_full + 16 * s + 8 * (warp >> 2), ph);
                float c0[4] = {0.f, 0.f, 0.f, 0.f}, c1[4] = {0.f, 0.f, 0.f, 0.f};
                const uint32_t kb = kbase + s * TILE;
#pragma unroll
                for (int q = 0; q < 4; q++) {
                    uint32_t a0[4], a1[4];
                    ldsm4(a0, (kb ^ (((2 * q) & 3) << 5)) + (q >> 1) * 1024);
                    ldsm4(a1, (kb ^ (((2 * q + 1) & 3) << 5)) + (q >> 1) * 1024);
                    mma16816(c0, a0, qb[q].x, qb[q].y);
                    mma16816(c1, a1, qb[q].z, qb[q].w);
                }
                __syncwarp();
                if (lane == 0) mbar_arrive(bar_empty + 8 * s);
                sts32(sc_addr + i * 1024, __float_as_uint(sel4(c0, j4) + sel4(c1, j4)));
                if (++s == NST) { s = 0; ph ^= 1; }
            }
        }
        mbar_wait(bar_ready, 0);
        bar_consumers();

        {
            constexpr float SCALE = 0.08838834764831845f * 1.4426950408889634f;
            const int hd = warp & 1, st = warp >> 1;
            float4 sv[4];
            float ms[4], sum[4];
#pragma unroll
            for (int t = 0; t < 4; t++) {
                sv[t] = lds128f(sb + SM_SC + ((4 * st + t) * 256 + g8 * 32 + hd * 16 + j4 * 4) * 4);
                ms[t] = fmaxf(fmaxf(sv[t].x, sv[t].y), fmaxf(sv[t].z, sv[t].w));
            }
#pragma unroll
            for (int o = 16; o > 0; o >>= 1)
#pragma unroll
                for (int t = 0; t < 4; t++) ms[t] = fmaxf(ms[t], __shfl_xor_sync(0xffffffffu, ms[t], o));
#pragma unroll
            for (int t = 0; t < 4; t++) {
                ms[t] *= SCALE;
                const float m = ms[t];
                const float p0 = ex2(fmaf(sv[t].x, SCALE, -m)), p1 = ex2(fmaf(sv[t].y, SCALE, -m));
                const float p2 = ex2(fmaf(sv[t].z, SCALE, -m)), p3 = ex2(fmaf(sv[t].w, SCALE, -m));
                sum[t] = (p0 + p1) + (p2 + p3);
                sts64(sb + SM_P + (4 * st + t) * 512 + (g8 >> 1) * 128 + hd * 64 + j4 * 16 + (g8 & 1) * 8, pack_bf16(p0, p1), pack_bf16(p2, p3));
            }
            bar_consumers();
#pragma unroll
            for (int o = 16; o > 0; o >>= 1)
#pragma unroll
                for (int t = 0; t < 4; t++) sum[t] += __shfl_xor_sync(0xffffffffu, sum[t], o);
            if (lane < 4)
                stg64(reinterpret_cast<float2*>(g_s.stat) + ((prob * 2 + hd) * 16 + 4 * st + lane) * 64 + c, nz(sel4(ms, lane)), nz(sel4(sum, lane)));
        }

        {
            const uint32_t vbase = sb + SM_RING + (m4 >> 1) * 2048 + (warp >> 2) * 1024 + l8 * 128 + (((2 * (warp & 3) + (m4 & 1)) ^ l8) << 4);
            float* const dst = reinterpret_cast<float*>(g_s.part) + (prob * 64 + 8 * (j4 & 1) + warp) * 4096 + c * 16 + g8 + 8 * (j4 >> 1);
            const int go_off = 6 - (c >> 4);
#pragma unroll 1
            for (int i = 0; i < 16; i++) {
                float c0[4] = {0.f, 0.f, 0.f, 0.f}, c1[4] = {0.f, 0.f, 0.f, 0.f};
                uint4 pb[4];
#pragma unroll
                for (int q = 0; q < 4; q++) pb[q] = lds128(sb + SM_P + i * 512 + q * 128 + frag_off);
                const uint32_t vb = vbase + s * TILE;
#pragma unroll
                for (int q = 0; q < 4; q++) {
                    uint32_t a0[4], a1[4];
                    if ((q & 1) == 0) mbar_wait(bar_full + 16 * s + 4 * q, ph);
                    ldsm4t(a0, vb + (2 * q) * 4096);
                    ldsm4t(a1, vb + (2 * q + 1) * 4096);
                    mma16816(c0, a0, pb[q].x, pb[q].y);
                    mma16816(c1, a1, pb[q].z, pb[q].w);
                }
                __syncwarp();
                if (lane == 0) mbar_arrive(bar_empty + 8 * s);
                stg32(dst + (i < 12 ? 3 - (i & 3) : (i & 3)) * (16 * 4096) + (i >> 2) * 1024, nz(sel4(c0, j4) + sel4(c1, j4)));
                if (tid == 0 && (i == 15 || (i >= go_off && ((i - go_off) & 3) == 0)))
                    mbar_arrive(bar_go + (i == 15 ? 24 : 2 * (i - go_off)));
                if (++s == NST) { s = 0; ph ^= 1; }
            }
        }
    }

    {
        float acc[2][4][4];
#pragma unroll
        for (int e = 0; e < 32; e++) (&acc[0][0][0])[e] = 0.f;
        const int rho = 9 * ((m4 >> 1) * 8 + l8) + warp;
        uint32_t base[4];
#pragma unroll
        for (int mt = 0; mt < 4; mt++) base[mt] = (sb + SM_RING + rho * 128 + (((m4 & 1) ^ (rho & 7)) << 4)) ^ (mt << 5);
        float4* dst = g_s.acc + (prob * 40 + (tid >> 3)) * 72 + (tid & 7);
        __nv_bfloat16* optr = prm.out + prob * 576 + warp * 64 + 16 * j4 + g8;
        uint32_t js = j4, of_addr = sb + SM_OF + (g8 & 1) * 128 + j4 * 32;
        asm volatile("" : "+r"(base[0]), "+r"(base[1]), "+r"(base[2]), "+r"(base[3]), "+l"(dst), "+l"(optr), "+r"(js), "+r"(of_addr));
        uint32_t wa[2][4][4];
#define LOAD_W(t) _Pragma("unroll") for (int mt = 0; mt < 4; mt++) ldsm4t(wa[(t) & 1][mt], base[mt] + (((t) + 5) % NST) * TILE)
#define MMA_W(t, b0, b1) _Pragma("unroll") for (int mt = 0; mt < 4; mt++) mma16816(acc[(t) & 1][mt], wa[(t) & 1][mt], b0, b1)
        auto pick = [&](int a, int e) {
            float r;
            asm("{\n .reg .pred p, q;\n .reg .f32 u, v;\n .reg .b32 t;\n and.b32 t, %5, 1;\n setp.ne.u32 p, t, 0;\n setp.gt.u32 q, %5, 1;\n"
                " selp.f32 u, %2, %1, p;\n selp.f32 v, %4, %3, p;\n selp.f32 %0, v, u, q;\n}"
                : "=f"(r) : "f"(acc[a][0][e]), "f"(acc[a][1][e]), "f"(acc[a][2][e]), "f"(acc[a][3][e]), "r"(js));
            return r;
        };
        mbar_wait(bar_ofa, 0);
        const uint4 o0 = lds128(of_addr);
        const float2 o1 = lds64f(of_addr + 16);
        mbar_wait(bar_full + 80, 1);
        LOAD_W(0);
        MMA_W(0, o0.x, o0.y);
        mbar_wait(bar_full, 0);
        LOAD_W(1);
        MMA_W(1, o0.z, o0.w);
        mbar_wait(bar_full + 16, 0);
        LOAD_W(2);
        const bool have_w = mbar_test(bar_full + 32, 0);
        if (have_w) { LOAD_W(3); }
        MMA_W(2, __float_as_uint(o1.x), __float_as_uint(o1.y));
        float2 o2;
        bool have_o = false;
        if (!have_w) {
            uint32_t n = 0;
            while (!mbar_test(bar_full + 32, 0)) {
                if (mbar_test(bar_of, 0)) {
                    o2 = lds64f(of_addr + 24);
                    have_o = true;
                    mbar_wait(bar_full + 32, 0);
                    break;
                }
                if (++n > (SPIN_LIMIT << 4)) __trap();
            }
            LOAD_W(3);
        }
        if (!have_o) { mbar_wait(bar_of, 0); o2 = lds64f(of_addr + 24); }
        MMA_W(3, __float_as_uint(o2.x), __float_as_uint(o2.y));
        const float v0 = (pick(0, 0) + pick(0, 1)) + (pick(1, 0) + pick(1, 1)), v1 = (pick(0, 2) + pick(0, 3)) + (pick(1, 2) + pick(1, 3));
        float r0, r1, r2;
        asm volatile("{\n .reg .f32 t;\n atom.relaxed.gpu.global.add.v4.f32 {%0,%1,%2,t}, [%3], {%4,%5,%6,%7};\n}"
                     : "=f"(r0), "=f"(r1), "=f"(r2) : "l"(dst), "f"(v0), "f"(v1), "f"(1.0f), "f"(0.0f) : "memory");
        if (r2 == 63.0f) {
            const uint32_t res = pack_bf16(r0 + v0, r1 + v1);
            asm volatile("st.global.u16 [%0], %1;\n st.global.u16 [%0 + 16], %2;" ::"l"(optr), "h"((uint16_t)res), "h"((uint16_t)(res >> 16)) : "memory");
        }
#undef LOAD_W
#undef MMA_W
    }
}

typedef CUresult (*EncodeFn)(CUtensorMap*, CUtensorMapDataType, cuuint32_t, void*, const cuuint64_t*, const cuuint64_t*,
                             const cuuint32_t*, const cuuint32_t*, CUtensorMapInterleave, CUtensorMapSwizzle,
                             CUtensorMapL2promotion, CUtensorMapFloatOOBfill);

}

extern "C" void kernel_launch(void* const* d_in, const int* in_sizes, int n_in, void* d_out, int out_size) {
    (void)in_sizes; (void)n_in; (void)out_size;
    static EncodeFn enc = nullptr;
    if (!enc) {
        cudaDriverEntryPointQueryResult qr;
        void* fn = nullptr;
        cudaGetDriverEntryPoint("cuTensorMapEncodeTiled", &fn, cudaEnableDefault, &qr);
        enc = (EncodeFn)fn;
        cudaFuncSetAttribute(gqa2_decode_kernel, cudaFuncAttributeMaxDynamicSharedMemorySize, SM_TOTAL);
    }
    Params prm;
    const cuuint32_t es[4] = {1, 1, 1, 1};
    for (int p = 0; p < 2; p++) {
        prm.x[p] = (const __nv_bfloat16*)d_in[5 * p + 0];
        void* ptr[4] = {d_in[5 * p + 3], d_in[5 * p + 1], d_in[5 * p + 2], d_in[5 * p + 4]};
        const cuuint64_t gd[4][4] = {{4096, 576, 1, 1}, {64, 8, 2, 16 * 8192 / 8}, {64, 8, 2, 16 * 8192 / 8}, {64, 4096 * 9, 1, 1}};
        const cuuint64_t gs[4][3] = {{8192, 8192 * 576, 8192 * 576}, {256, 128, 2048}, {256, 128, 2048}, {128, 128 * 4096 * 9, 128 * 4096 * 9}};
        const cuuint32_t bd[4][4] = {{64, 96, 1, 1}, {64, 8, 2, 8}, {64, 8, 2, 8}, {64, 144, 1, 1}};
        for (int i = 0; i < 4; i++)
            enc(&prm.tm[p][i], CU_TENSOR_MAP_DATA_TYPE_BFLOAT16, 4, ptr[i], gd[i], gs[i], bd[i], es,
                CU_TENSOR_MAP_INTERLEAVE_NONE, CU_TENSOR_MAP_SWIZZLE_128B, CU_TENSOR_MAP_L2_PROMOTION_L2_128B,
                CU_TENSOR_MAP_FLOAT_OOB_FILL_NONE);
    }
    prm.out = (__nv_bfloat16*)d_out;
    gqa2_decode_kernel<<<128, NTHREADS, SM_TOTAL>>>(prm);
}
```
